```python
import torch

def _softmax(x, axis=-1):
    return torch.softmax(x, dim=axis)
def _gelu(x):
    return torch.nn.functional.gelu(x, approximate="tanh")
def _silu(x):
    return torch.nn.functional.silu(x)
def _sigmoid(x):
    return torch.sigmoid(x)
def _layernorm(x, axis=-1, eps=1e-5):
    m = x.mean(dim=axis, keepdim=True)
    v = x.var(dim=axis, keepdim=True, unbiased=False)
    return (x - m) / torch.sqrt(v + eps)
def _scatter_add(tgt, idx, src, axis=0):
    return tgt.clone().index_add_(axis, idx, src)
def _segment_sum(src, seg, n):
    out = torch.zeros((n,) + src.shape[1:], dtype=src.dtype)
    return out.index_add_(0, seg, src)
def _pad(x, pw):
    flat = tuple(v for pair in reversed(pw) for v in pair)
    return torch.nn.functional.pad(x, flat)

kernel_name = 'sequential_preLN__linear_attn_block__glu_gated_glu__prompt'

def setup_inputs():

    _w = (lambda a: (lambda t: t.to(torch.bfloat16) if t.is_floating_point() else t)(torch.as_tensor(a)))
    def _A_setup():
        B, S, D = 1, 2048, 448
        return {
            "x": _w((lambda *s: torch.randn(*s, dtype=torch.bfloat16) * 0.05)(B, S, D)),
            "wqkv": _w((lambda *s: torch.randn(*s, dtype=torch.bfloat16) * 0.1)(D, 3 * D)),
            "wo": _w((lambda *s: torch.randn(*s, dtype=torch.bfloat16) * 0.05)(D, D)),
        }
    _A_in = _A_setup()

    def _B_setup():
        B, S, D, F = 1, 2048, 448, 1792
        return {
            "x": _w((lambda *s: torch.randn(*s, dtype=torch.bfloat16) * 0.05)(B, S, D)),
            "w_gate": _w((lambda *s: torch.randn(*s, dtype=torch.bfloat16) * 0.05)(D, F)),
            "w_up": _w((lambda *s: torch.randn(*s, dtype=torch.bfloat16) * 0.05)(D, F)),
            "w_down": _w((lambda *s: torch.randn(*s, dtype=torch.bfloat16) * 0.05)(F, D)),
        }
    _B_in = _B_setup()

    return {
        "A_x": _A_in["x"],
        "A_wqkv": _A_in["wqkv"],
        "A_wo": _A_in["wo"],
        "B_x": _B_in["x"],
        "B_w_gate": _B_in["w_gate"],
        "B_w_up": _B_in["w_up"],
        "B_w_down": _B_in["w_down"],
    }

def reference(A_x, A_wqkv, A_wo, B_x, B_w_gate, B_w_up, B_w_down):
    def _A_ref(x, wqkv, wo):
        B, S, D = x.shape
        H = 16; Dh = D // H
        qkv = (lambda x, *d: x.permute(*d))((x @ wqkv).reshape(B, S, 3, H, Dh), 2, 0, 3, 1, 4)
        q, k, v = qkv[0], qkv[1], qkv[2]
        phi = lambda t: torch.where(t > 0, t + 1, torch.exp(t)) + 1e-6
        pq, pk = phi(q), phi(k)
        kv = torch.einsum("bhsd,bhse->bhde", pk, v)
        z = torch.einsum("bhsd->bhd", pk)
        num = torch.einsum("bhqd,bhde->bhqe", pq, kv)
        den = torch.einsum("bhqd,bhd->bhq", pq, z)[..., None] + 1e-6
        o = num / den
        return (lambda x, *d: x.permute(*d))(o, 0, 2, 1, 3).reshape(B, S, D) @ wo

    def _B_ref(x, w_gate, w_up, w_down):
        g = torch.einsum("bsd,df->bsf", x, w_gate)
        u = torch.einsum("bsd,df->bsf", x, w_up)
        h = _sigmoid(g) * u
        return torch.einsum("bsf,fd->bsd", h, w_down)

    x = A_x
    h = x + _A_ref(_layernorm(x, axis=-1), A_wqkv, A_wo)
    h2 = h + _B_ref(_layernorm(h, axis=-1), B_w_gate, B_w_up, B_w_down)
    return h2
```

```cpp
#include <cuda_runtime.h>
#include <cuda_bf16.h>
#include <cuda.h>
#include <stdint.h>

template <uint32_t HI>
__device__ __forceinline__ void wgmma_ss_n64(float (&d)[32], uint32_t da, uint32_t db, int scale_d) {
  asm volatile("{\n.reg .pred p;\n.reg .b64 da, db;\nsetp.ne.b32 p, %34, 0;\n"
    "mov.b64 db, {%33, %35};\n"
    "mov.b64 da, {%32, %35};\n"
    "wgmma.mma_async.sync.aligned.m64n64k16.f32.bf16.bf16 "
    "{%0, %1, %2, %3, %4, %5, %6, %7, %8, %9, %10, %11, %12, %13, %14, %15, %16, %17, %18, %19, %20, %21, %22, %23, %24, %25, %26, %27, %28, %29, %30, %31}, "
    "da, db, p, 1, 1, 1, 1;\n}\n"
    : "+f"(d[0]), "+f"(d[1]), "+f"(d[2]), "+f"(d[3]), "+f"(d[4]), "+f"(d[5]), "+f"(d[6]), "+f"(d[7]), "+f"(d[8]), "+f"(d[9]), "+f"(d[10]), "+f"(d[11]), "+f"(d[12]), "+f"(d[13]), "+f"(d[14]), "+f"(d[15]), "+f"(d[16]), "+f"(d[17]), "+f"(d[18]), "+f"(d[19]), "+f"(d[20]), "+f"(d[21]), "+f"(d[22]), "+f"(d[23]), "+f"(d[24]), "+f"(d[25]), "+f"(d[26]), "+f"(d[27]), "+f"(d[28]), "+f"(d[29]), "+f"(d[30]), "+f"(d[31])
    : "r"(da), "r"(db), "r"(scale_d), "n"(HI));
}
template <uint32_t HI>
__device__ __forceinline__ void wgmma_rs_n32(float (&d)[16], const uint32_t a0, const uint32_t a1, const uint32_t a2, const uint32_t a3, uint32_t db, int scale_d) {
  asm volatile("{\n.reg .pred p;\n.reg .b64 da, db;\nsetp.ne.b32 p, %21, 0;\n"
    "mov.b64 db, {%20, %22};\n"
    "wgmma.mma_async.sync.aligned.m64n32k16.f32.bf16.bf16 "
    "{%0, %1, %2, %3, %4, %5, %6, %7, %8, %9, %10, %11, %12, %13, %14, %15}, "
    "{%16, %17, %18, %19}, db, p, 1, 1, %23;\n}\n"
    : "+f"(d[0]), "+f"(d[1]), "+f"(d[2]), "+f"(d[3]), "+f"(d[4]), "+f"(d[5]), "+f"(d[6]), "+f"(d[7]), "+f"(d[8]), "+f"(d[9]), "+f"(d[10]), "+f"(d[11]), "+f"(d[12]), "+f"(d[13]), "+f"(d[14]), "+f"(d[15])
    : "r"(a0), "r"(a1), "r"(a2), "r"(a3), "r"(db), "r"(scale_d), "n"(HI), "n"(HI >> 30 ? 1 : 0));
}
template <uint32_t HI>
__device__ __forceinline__ void wgmma_rs_n56(float (&d)[28], const uint32_t a0, const uint32_t a1, const uint32_t a2, const uint32_t a3, uint32_t db, int scale_d) {
  asm volatile("{\n.reg .pred p;\n.reg .b64 da, db;\nsetp.ne.b32 p, %33, 0;\n"
    "mov.b64 db, {%32, %34};\n"
    "wgmma.mma_async.sync.aligned.m64n56k16.f32.bf16.bf16 "
    "{%0, %1, %2, %3, %4, %5, %6, %7, %8, %9, %10, %11, %12, %13, %14, %15, %16, %17, %18, %19, %20, %21, %22, %23, %24, %25, %26, %27}, "
    "{%28, %29, %30, %31}, db, p, 1, 1, %35;\n}\n"
    : "+f"(d[0]), "+f"(d[1]), "+f"(d[2]), "+f"(d[3]), "+f"(d[4]), "+f"(d[5]), "+f"(d[6]), "+f"(d[7]), "+f"(d[8]), "+f"(d[9]), "+f"(d[10]), "+f"(d[11]), "+f"(d[12]), "+f"(d[13]), "+f"(d[14]), "+f"(d[15]), "+f"(d[16]), "+f"(d[17]), "+f"(d[18]), "+f"(d[19]), "+f"(d[20]), "+f"(d[21]), "+f"(d[22]), "+f"(d[23]), "+f"(d[24]), "+f"(d[25]), "+f"(d[26]), "+f"(d[27])
    : "r"(a0), "r"(a1), "r"(a2), "r"(a3), "r"(db), "r"(scale_d), "n"(HI), "n"(HI >> 30 ? 1 : 0));
}
template <uint32_t HI>
__device__ __forceinline__ void wgmma_rs_n64(float (&d)[32], const uint32_t a0, const uint32_t a1, const uint32_t a2, const uint32_t a3, uint32_t db, int scale_d) {
  asm volatile("{\n.reg .pred p;\n.reg .b64 da, db;\nsetp.ne.b32 p, %37, 0;\n"
    "mov.b64 db, {%36, %38};\n"
    "wgmma.mma_async.sync.aligned.m64n64k16.f32.bf16.bf16 "
    "{%0, %1, %2, %3, %4, %5, %6, %7, %8, %9, %10, %11, %12, %13, %14, %15, %16, %17, %18, %19, %20, %21, %22, %23, %24, %25, %26, %27, %28, %29, %30, %31}, "
    "{%32, %33, %34, %35}, db, p, 1, 1, %39;\n}\n"
    : "+f"(d[0]), "+f"(d[1]), "+f"(d[2]), "+f"(d[3]), "+f"(d[4]), "+f"(d[5]), "+f"(d[6]), "+f"(d[7]), "+f"(d[8]), "+f"(d[9]), "+f"(d[10]), "+f"(d[11]), "+f"(d[12]), "+f"(d[13]), "+f"(d[14]), "+f"(d[15]), "+f"(d[16]), "+f"(d[17]), "+f"(d[18]), "+f"(d[19]), "+f"(d[20]), "+f"(d[21]), "+f"(d[22]), "+f"(d[23]), "+f"(d[24]), "+f"(d[25]), "+f"(d[26]), "+f"(d[27]), "+f"(d[28]), "+f"(d[29]), "+f"(d[30]), "+f"(d[31])
    : "r"(a0), "r"(a1), "r"(a2), "r"(a3), "r"(db), "r"(scale_d), "n"(HI), "n"(HI >> 30 ? 1 : 0));
}
template <uint32_t HI>
__device__ __forceinline__ void wgmma_rs_n96(float (&d)[48], const uint32_t a0, const uint32_t a1, const uint32_t a2, const uint32_t a3, uint32_t db, int scale_d) {
  asm volatile("{\n.reg .pred p;\n.reg .b64 da, db;\nsetp.ne.b32 p, %53, 0;\n"
    "mov.b64 db, {%52, %54};\n"
    "wgmma.mma_async.sync.aligned.m64n96k16.f32.bf16.bf16 "
    "{%0, %1, %2, %3, %4, %5, %6, %7, %8, %9, %10, %11, %12, %13, %14, %15, %16, %17, %18, %19, %20, %21, %22, %23, %24, %25, %26, %27, %28, %29, %30, %31, %32, %33, %34, %35, %36, %37, %38, %39, %40, %41, %42, %43, %44, %45, %46, %47}, "
    "{%48, %49, %50, %51}, db, p, 1, 1, %55;\n}\n"
    : "+f"(d[0]), "+f"(d[1]), "+f"(d[2]), "+f"(d[3]), "+f"(d[4]), "+f"(d[5]), "+f"(d[6]), "+f"(d[7]), "+f"(d[8]), "+f"(d[9]), "+f"(d[10]), "+f"(d[11]), "+f"(d[12]), "+f"(d[13]), "+f"(d[14]), "+f"(d[15]), "+f"(d[16]), "+f"(d[17]), "+f"(d[18]), "+f"(d[19]), "+f"(d[20]), "+f"(d[21]), "+f"(d[22]), "+f"(d[23]), "+f"(d[24]), "+f"(d[25]), "+f"(d[26]), "+f"(d[27]), "+f"(d[28]), "+f"(d[29]), "+f"(d[30]), "+f"(d[31]), "+f"(d[32]), "+f"(d[33]), "+f"(d[34]), "+f"(d[35]), "+f"(d[36]), "+f"(d[37]), "+f"(d[38]), "+f"(d[39]), "+f"(d[40]), "+f"(d[41]), "+f"(d[42]), "+f"(d[43]), "+f"(d[44]), "+f"(d[45]), "+f"(d[46]), "+f"(d[47])
    : "r"(a0), "r"(a1), "r"(a2), "r"(a3), "r"(db), "r"(scale_d), "n"(HI), "n"(HI >> 30 ? 1 : 0));
}
template <uint32_t HI>
__device__ __forceinline__ void wgmma_rs_n128(float (&d)[64], const uint32_t a0, const uint32_t a1, const uint32_t a2, const uint32_t a3, uint32_t db, int scale_d) {
  asm volatile("{\n.reg .pred p;\n.reg .b64 da, db;\nsetp.ne.b32 p, %69, 0;\n"
    "mov.b64 db, {%68, %70};\n"
    "wgmma.mma_async.sync.aligned.m64n128k16.f32.bf16.bf16 "
    "{%0, %1, %2, %3, %4, %5, %6, %7, %8, %9, %10, %11, %12, %13, %14, %15, %16, %17, %18, %19, %20, %21, %22, %23, %24, %25, %26, %27, %28, %29, %30, %31, %32, %33, %34, %35, %36, %37, %38, %39, %40, %41, %42, %43, %44, %45, %46, %47, %48, %49, %50, %51, %52, %53, %54, %55, %56, %57, %58, %59, %60, %61, %62, %63}, "
    "{%64, %65, %66, %67}, db, p, 1, 1, %71;\n}\n"
    : "+f"(d[0]), "+f"(d[1]), "+f"(d[2]), "+f"(d[3]), "+f"(d[4]), "+f"(d[5]), "+f"(d[6]), "+f"(d[7]), "+f"(d[8]), "+f"(d[9]), "+f"(d[10]), "+f"(d[11]), "+f"(d[12]), "+f"(d[13]), "+f"(d[14]), "+f"(d[15]), "+f"(d[16]), "+f"(d[17]), "+f"(d[18]), "+f"(d[19]), "+f"(d[20]), "+f"(d[21]), "+f"(d[22]), "+f"(d[23]), "+f"(d[24]), "+f"(d[25]), "+f"(d[26]), "+f"(d[27]), "+f"(d[28]), "+f"(d[29]), "+f"(d[30]), "+f"(d[31]), "+f"(d[32]), "+f"(d[33]), "+f"(d[34]), "+f"(d[35]), "+f"(d[36]), "+f"(d[37]), "+f"(d[38]), "+f"(d[39]), "+f"(d[40]), "+f"(d[41]), "+f"(d[42]), "+f"(d[43]), "+f"(d[44]), "+f"(d[45]), "+f"(d[46]), "+f"(d[47]), "+f"(d[48]), "+f"(d[49]), "+f"(d[50]), "+f"(d[51]), "+f"(d[52]), "+f"(d[53]), "+f"(d[54]), "+f"(d[55]), "+f"(d[56]), "+f"(d[57]), "+f"(d[58]), "+f"(d[59]), "+f"(d[60]), "+f"(d[61]), "+f"(d[62]), "+f"(d[63])
    : "r"(a0), "r"(a1), "r"(a2), "r"(a3), "r"(db), "r"(scale_d), "n"(HI), "n"(HI >> 30 ? 1 : 0));
}

namespace {

constexpr int DM = 448, FF = 1792, SEQ = 2048;
constexpr uint32_t SLOT = 28672;
constexpr uint32_t BLK = 14336;
constexpr uint32_t BAR_OFF = 8 * SLOT;
constexpr uint32_t SMEM_BYTES = BAR_OFF + 1280;
constexpr int SPIN_LIMIT = 1 << 18;
#define JMAP(b) (((b) >> 4) & 7)
#define RBMAP(b) ((b) & 15)

#define VMAP 1
__device__ __forceinline__ int vbid(int b) {
  if (VMAP == 0) return b;
  int v;
  asm("{\n.reg .pred p, q;\n.reg .s32 t, u;\nmad.lo.s32 t, %1, 37, -2146;\nshr.s32 t, t, 9;\nsetp.lt.s32 p, %1, 72;\n"
      "shr.s32 u, %1, 1;\nmad.lo.s32 u, u, 7, 36;\nsetp.lt.s32 q, %1, 8;\nselp.s32 u, u, 0, q;\nselp.s32 t, u, t, p;\n"
      "mad.lo.s32 t, t, 2, %1;\nand.b32 %0, t, 127;\n}" : "=r"(v) : "r"(b));
  return v;
}
#define VBID vbid(blockIdx.x)

enum Bar : int {
  XF = 0,
  WS = 7,
  WV = 11,
  WQ0 = 15, WQ1, WO0, WO1, HAF, HBF,
  GUF = 21,
  WDF = 27,
  OF = 31,
  HF = 39,
  KF = 47,
  IN = 49, EP, ZF, RS,
  WE = 53,
  HE = 55,
  MR = 57,
  KM = 59,
  QE = 60, WOE0, WOE1, HHE,
  GUM = 64,
  GUE = 66,
  XE = 69, KE,
  DE,
  RD,
  KD,
  SD,
  NBAR = SD + 2
};
#define OV 0
#define ORD 100, 0, 101, 1, 102, 2, 103, 3, 104, 4, 105, 5, 6, 7
#define EL 0
#define TH 1
#define PIN 6
#define UP 0
#define TB 0
#define ZI 0
#define DG 2
#define DS 0
#define TC 1
#define DR 0
#define L1 0
#define DC 2
#define EH KM
#define AH 0
#define AC 0
#define H2 0
#define O5 0
#define NT 0
#define KMC 0
#define G2 0
#define G3 DE
#define EU 1
#define RL 8
#define LS 5
#define RP KE
#define WV_ 1
#define IL 0
#define IH 0
#define HB3 1
#define EBP 1
#define OWN 1
#define MG 1
#define T0 0
#define PFT (WV + 3)
#define PFD MR
#define B2 0
#define DQ WV
#define QP 27
#define PSTART -1
#define RSTART KM
#define ZSTART KM
#define HG RD
#define HINT -1
#define KALL 1
#define KW -1
#define PEEL 1
#define SLOWP 1
#define GW 0
#define PP 1
#define CALL 0
#define FP 1
#define HP0 3
#define TOPR 1
#define K8 1
#define DLY 1
#define WG 0
#define WW 3
#define EB 1
#define W0 1
#define UG 0
#define N96 0
#define SG 2
#define TP 13
#define TQ 13
#define TD 13
#define TE -1
#define LO0 -1
#define R2 13
#define RW 5
#define DW 7
#define NH 10
#define C7 1
#define FQ 2
#define RA 1
#define CO 3
#define SO 1
#define MO 1
#define LP 0
#define TF 8
#define RHI 232
#define RLO 40
constexpr uint32_t MST_OFF = BAR_OFF + 768;

constexpr uint32_t Z_OFF = BAR_OFF + 1024;

struct alignas(64) Maps {
  CUtensorMap x, wkv, wqkv, wo, wg, wu, wg32, wu32, wd, wd32, out, out32;
};

constexpr uint32_t HB = 8192;
constexpr uint32_t CB = C7 ? 7424 : HB;
constexpr uint32_t KVP = 224;
#define R4(...) __VA_ARGS__, __VA_ARGS__, __VA_ARGS__, __VA_ARGS__
#define R7(...) R4(__VA_ARGS__), __VA_ARGS__, __VA_ARGS__, __VA_ARGS__
__device__ __align__(128) uint4 g_kv[2 * 8 * KVP] = {R4(R4(R7(R4(R4({0, 0, 0, 0xC1800000u})), R4(R4({0, 0, 0, 0xC180u})))))};
__device__ __align__(128) float2 g_z[2][8][64];
__device__ uint4 g_x[512 * (HB / 16)];
__device__ uint4 g_rs[DM / 4];
__device__ uint4 g_h[128 * 14 * 256];
__device__ unsigned g_ep[128 * 32];
__constant__ uint32_t c_off[56] = {0, 8, 2048, 2056, 4096, 4104, 6144, 22528, 16384, 16392, 18432, 18440, 20480, 20488, 32768, 32776, 34816, 34824, 36864, 36872, 38912, 55296, 49152, 49160, 51200, 51208, 53248, 53256, 65536, 65544, 67584, 67592, 69632, 69640, 71680, 88064, 81920, 81928, 83968, 83976, 86016, 86024, 98304, 98312, 100352, 100360, 102400, 102408, 104448, 120832, 114688, 114696, 116736, 116744, 118784, 118792};
__device__ unsigned g_flag[1024 + 16 * 32];
#define TS(role, i) do {} while (0)
#define TS2(i) do {} while (0)
#define COUNT_FALLBACK(i) do {} while (0)

#define TSD(i) do {} while (0)
#define TSM(i) do {} while (0)
#define TSH(i) do {} while (0)
#define TSG(i) do {} while (0)
#define TSR(i) do {} while (0)
#define TSY(r, i) do {} while (0)
#define TSA(r, i) TS(r, i)
#define TSB(r, i) do {} while (0)
__device__ __forceinline__ uint32_t smem_u32(const void* p) { return (uint32_t)__cvta_generic_to_shared(p); }
__device__ __forceinline__ bool elect() {
  uint32_t r;
  asm volatile("{\n.reg .pred p;\nelect.sync _|p, 0xffffffff;\nselp.u32 %0, 1, 0, p;\n}" : "=r"(r));
  return r;
}
__device__ __forceinline__ void mbar_init(uint32_t bar, uint32_t cnt) {
  asm volatile("mbarrier.init.shared::cta.b64 [%0], %1;" ::"r"(bar), "r"(cnt) : "memory");
}
__device__ __forceinline__ void mbar_expect(uint32_t bar, uint32_t bytes) {
  asm volatile("mbarrier.arrive.expect_tx.shared::cta.b64 _, [%0], %1;" ::"r"(bar), "r"(bytes) : "memory");
}
__device__ __forceinline__ void mbar_arrive(uint32_t bar) {
  asm volatile("mbarrier.arrive.shared::cta.b64 _, [%0];" ::"r"(bar) : "memory");
}
__device__ __forceinline__ bool mbar_test(uint32_t bar) {
  uint32_t done;
  asm volatile("{\n.reg .pred p;\nmbarrier.test_wait.parity.shared::cta.b64 p, [%1], 0;\nselp.u32 %0, 1, 0, p;\n}"
               : "=r"(done) : "r"(bar) : "memory");
  return done;
}
__device__ __forceinline__ void mbar_wait(uint32_t bar) {
  asm volatile("{\n.reg .pred p, q;\n.reg .u32 c;\nmov.u32 c, 0;\n"
               "WAIT_LOOP:\nadd.u32 c, c, 1;\nmbarrier.try_wait.parity.shared::cta.b64 p, [%0], 0;\n"
               "setp.lt.and.u32 q, c, 262144, !p;\n@q bra WAIT_LOOP;\n}" ::"r"(bar) : "memory");
}
__device__ __forceinline__ void tma2d(uint32_t dst, const CUtensorMap* tm, int c0, int c1, uint32_t bar) {
  asm volatile("cp.async.bulk.tensor.2d.shared::cluster.global.mbarrier::complete_tx::bytes [%0], [%1, {%3, %4}], [%2];"
               ::"r"(dst), "l"(tm), "r"(bar), "r"(c0), "r"(c1) : "memory");
}
__device__ __forceinline__ void bulk_load(uint32_t dst, const void* src, uint32_t bytes, uint32_t bar) {
  asm volatile("cp.async.bulk.shared::cluster.global.mbarrier::complete_tx::bytes [%0], [%1], %2, [%3];"
               ::"r"(dst), "l"(src), "r"(bytes), "r"(bar) : "memory");
}
__device__ __forceinline__ void bulk_load_mc(uint32_t dst, const void* src, uint32_t bytes, uint32_t bar, uint16_t mask) {
  asm volatile("cp.async.bulk.shared::cluster.global.mbarrier::complete_tx::bytes.multicast::cluster [%0], [%1], %2, [%3], %4;"
               ::"r"(dst), "l"(src), "r"(bytes), "r"(bar), "h"(mask) : "memory");
}
__device__ __forceinline__ void l2_prefetch(const void* src, uint32_t bytes) {
  asm volatile("cp.async.bulk.prefetch.L2.global [%0], %1;" ::"l"(src), "r"(bytes) : "memory");
}
__device__ __forceinline__ void fence_async_smem() { asm volatile("fence.proxy.async.shared::cta;" ::: "memory"); }
__device__ __forceinline__ void wg_fence() { asm volatile("wgmma.fence.sync.aligned;" ::: "memory"); }
__device__ __forceinline__ void wg_commit() { asm volatile("wgmma.commit_group.sync.aligned;" ::: "memory"); }
template <int N> __device__ __forceinline__ void wg_wait() { asm volatile("wgmma.wait_group.sync.aligned %0;" ::"n"(N) : "memory"); }
__device__ __forceinline__ void bar_sync(int id, int n) { asm volatile("bar.sync %0, %1;" ::"r"(id), "r"(n) : "memory"); }
__device__ __forceinline__ void bar_arrive(int id, int n) { asm volatile("bar.arrive %0, %1;" ::"r"(id), "r"(n) : "memory"); }
constexpr uint32_t H128 = (1024u >> 4) | (1u << 30), H64 = (512u >> 4) | (2u << 30);
constexpr uint32_t HK = 512u >> 4;
__device__ __forceinline__ constexpr uint32_t dlo(uint32_t addr, uint32_t lbo) { return (addr >> 4) | ((lbo >> 4) << 16); }
__device__ __forceinline__ void ldsm4(uint32_t addr, uint32_t& r0, uint32_t& r1, uint32_t& r2, uint32_t& r3) {
  asm volatile("ldmatrix.sync.aligned.m8n8.x4.shared.b16 {%0, %1, %2, %3}, [%4];"
               : "=r"(r0), "=r"(r1), "=r"(r2), "=r"(r3) : "r"(addr) : "memory");
}
__device__ __forceinline__ void stsm4(uint32_t addr, uint32_t r0, uint32_t r1, uint32_t r2, uint32_t r3) {
  asm volatile("stmatrix.sync.aligned.m8n8.x4.shared.b16 [%0], {%1, %2, %3, %4};"
               ::"r"(addr), "r"(r0), "r"(r1), "r"(r2), "r"(r3) : "memory");
}
__device__ __forceinline__ void ldsm4t(uint32_t addr, uint32_t& r0, uint32_t& r1, uint32_t& r2, uint32_t& r3) {
  asm volatile("ldmatrix.sync.aligned.m8n8.x4.trans.shared.b16 {%0, %1, %2, %3}, [%4];"
               : "=r"(r0), "=r"(r1), "=r"(r2), "=r"(r3) : "r"(addr) : "memory");
}
__device__ __forceinline__ void stsm4t(uint32_t addr, uint32_t r0, uint32_t r1, uint32_t r2, uint32_t r3) {
  asm volatile("stmatrix.sync.aligned.m8n8.x4.trans.shared.b16 [%0], {%1, %2, %3, %4};"
               ::"r"(addr), "r"(r0), "r"(r1), "r"(r2), "r"(r3) : "memory");
}
__device__ __forceinline__ void lds128(uint32_t addr, uint32_t& r0, uint32_t& r1, uint32_t& r2, uint32_t& r3) {
  asm volatile("ld.shared.v4.u32 {%0, %1, %2, %3}, [%4];" : "=r"(r0), "=r"(r1), "=r"(r2), "=r"(r3) : "r"(addr) : "memory");
}
__device__ __forceinline__ void lds64(uint32_t addr, uint32_t& r0, uint32_t& r1) {
  asm volatile("ld.shared.v2.u32 {%0, %1}, [%2];" : "=r"(r0), "=r"(r1) : "r"(addr) : "memory");
}
__device__ __forceinline__ void sts128(uint32_t addr, uint32_t r0, uint32_t r1, uint32_t r2, uint32_t r3) {
  asm volatile("st.shared.v4.u32 [%0], {%1, %2, %3, %4};" ::"r"(addr), "r"(r0), "r"(r1), "r"(r2), "r"(r3) : "memory");
}
__device__ __forceinline__ uint32_t pack2(float lo, float hi) {
  uint32_t r;
  asm("cvt.rn.bf16x2.f32 %0, %1, %2;" : "=r"(r) : "f"(hi), "f"(lo));
  return r;
}
__device__ __forceinline__ uint32_t sub2v(uint32_t a, uint32_t b) {
  uint32_t r;
  asm volatile("sub.rn.bf16x2 %0, %1, %2;" : "=r"(r) : "r"(a), "r"(b));
  return r;
}
__device__ __forceinline__ uint32_t sub2(uint32_t a, uint32_t b) {
  uint32_t r;
  asm("sub.rn.bf16x2 %0, %1, %2;" : "=r"(r) : "r"(a), "r"(b));
  return r;
}
__device__ __forceinline__ uint32_t mul2(uint32_t a, uint32_t b) {
  uint32_t r;
  asm("mul.rn.bf16x2 %0, %1, %2;" : "=r"(r) : "r"(a), "r"(b));
  return r;
}
__device__ __forceinline__ uint32_t add2(uint32_t a, uint32_t b) {
  uint32_t r;
  asm("add.rn.bf16x2 %0, %1, %2;" : "=r"(r) : "r"(a), "r"(b));
  return r;
}
__device__ __forceinline__ uint32_t fma2(uint32_t a, uint32_t c) {
  uint32_t r;
  asm("fma.rn.bf16x2 %0, %1, %1, %2;" : "=r"(r) : "r"(a), "r"(c));
  return r;
}
__device__ __forceinline__ float bf_lo(uint32_t v) { return __uint_as_float(v << 16); }
__device__ __forceinline__ float bf_hi(uint32_t v) { return __uint_as_float(v & 0xFFFF0000u); }
__device__ __forceinline__ float ex2f(float x) { float r; asm("ex2.approx.ftz.f32 %0, %1;" : "=f"(r) : "f"(x)); return r; }
__device__ __forceinline__ float rcpf(float x) { float r; asm("rcp.approx.ftz.f32 %0, %1;" : "=f"(r) : "f"(x)); return r; }
__device__ __forceinline__ float tanhf_(float x) { float r; asm("tanh.approx.f32 %0, %1;" : "=f"(r) : "f"(x)); return r; }
__device__ __forceinline__ float phi(float a, float r, float r2) {
  return fmaf(fmaxf(a, 0.f), r, __saturatef(ex2f(a * r2) + 1e-6f));
}
__device__ __forceinline__ void pred_arrive(uint32_t bar, bool p) {
  asm volatile("{\n.reg .pred p;\nsetp.ne.u32 p, %1, 0;\n@p mbarrier.arrive.shared::cta.b64 _, [%0];\n}" ::"r"(bar), "r"((uint32_t)p) : "memory");
}
__device__ __forceinline__ void warp_arrive(uint32_t bar, int lane) {
  __syncwarp();
  pred_arrive(bar, lane == 0);
}
__device__ __forceinline__ void warp_arrive2(uint32_t bar, int lane) {
  __syncwarp();
  asm volatile("{\n.reg .pred p;\nsetp.eq.u32 p, %2, 0;\n@p mbarrier.arrive.shared::cta.b64 _, [%0];\n"
               "@p mbarrier.arrive.shared::cluster.b64 _, [%1];\n}" ::"r"(bar), "r"(bar ^ 0x1000000u), "r"(lane) : "memory");
}
__device__ __forceinline__ void pred_bar_arrive(int id, bool p) {
  asm volatile("{\n.reg .pred p;\nsetp.ne.u32 p, %1, 0;\n@p bar.arrive %0, 256;\n}" ::"r"(id), "r"((uint32_t)p) : "memory");
}
__device__ __forceinline__ void turn_wait(bool p) {
  asm volatile("{\n.reg .pred p;\nsetp.ne.u32 p, %0, 0;\n@p bar.sync 4, 256;\n@!p bar.sync 7, 256;\n}" ::"r"((uint32_t)p) : "memory");
}
__device__ __forceinline__ void tma2d_mc(uint32_t dst, const CUtensorMap* tm, int c0, int c1, uint32_t bar) {
  asm volatile("cp.async.bulk.tensor.2d.shared::cluster.global.mbarrier::complete_tx::bytes.multicast::cluster [%0], [%1, {%3, %4}], [%2], %5;"
               ::"r"(dst), "l"(tm), "r"(bar), "r"(c0), "r"(c1), "h"((uint16_t)3) : "memory");
}
__device__ __forceinline__ void tma4d_mc(uint32_t dst, const CUtensorMap* tm, int c0, int c2, uint32_t bar) {
  asm volatile("cp.async.bulk.tensor.4d.shared::cluster.global.mbarrier::complete_tx::bytes.multicast::cluster [%0], [%1, {%3, %6, %4, %6}], [%2], %5;"
               ::"r"(dst), "l"(tm), "r"(bar), "r"(c0), "r"(c2), "h"((uint16_t)3), "r"(0) : "memory");
}
__device__ __forceinline__ void mma16(float (&d)[4], uint32_t a0, uint32_t a1, uint32_t a2, uint32_t a3, uint32_t b0, uint32_t b1) {
  asm volatile("mma.sync.aligned.m16n8k16.row.col.f32.bf16.bf16.f32 {%0, %1, %2, %3}, {%4, %5, %6, %7}, {%8, %9}, {%0, %1, %2, %3};"
               : "+f"(d[0]), "+f"(d[1]), "+f"(d[2]), "+f"(d[3]) : "r"(a0), "r"(a1), "r"(a2), "r"(a3), "r"(b0), "r"(b1));
}
__device__ __forceinline__ void ldsm2(uint32_t addr, uint32_t& r0, uint32_t& r1) {
  asm volatile("ldmatrix.sync.aligned.m8n8.x2.shared.b16 {%0, %1}, [%2];" : "=r"(r0), "=r"(r1) : "r"(addr) : "memory");
}
__device__ __forceinline__ unsigned ld_rlx(const unsigned* p) {
  unsigned v;
  asm volatile("ld.relaxed.gpu.global.u32 %0, [%1];" : "=r"(v) : "l"(p) : "memory");
  return v;
}
__device__ __forceinline__ void warp_red(unsigned* p, int lane) {
  asm volatile("{\n.reg .pred p;\nsetp.eq.u32 p, %1, 0;\n@p red.relaxed.gpu.global.add.u32 [%0], 1;\n}" ::"l"(RA ? p + lane : p), "r"(lane) : "memory");
}
__device__ __forceinline__ void tma_red(const CUtensorMap* tm, int c0, int c1, uint32_t src, bool pr) {
  asm volatile("{\n.reg .pred p;\nsetp.ne.u32 p, %4, 0;\n"
               "@p cp.reduce.async.bulk.tensor.2d.global.shared::cta.add.tile.bulk_group [%0, {%1, %2}], [%3];\n}"
               ::"l"(tm), "r"(c0), "r"(c1), "r"(src), "r"((uint32_t)pr) : "memory");
}
__device__ __forceinline__ void red8(uint4* p, uint32_t a, uint32_t b, uint32_t c, uint32_t d, bool pr) {
  asm volatile("{\n.reg .pred p;\nsetp.ne.u32 p, %5, 0;\n@p red.relaxed.gpu.global.add.noftz.v4.bf16x2 [%0], {%1, %2, %3, %4};\n}"
               ::"l"(p), "r"(a), "r"(b), "r"(c), "r"(d), "r"((uint32_t)pr) : "memory");
}
__device__ __forceinline__ void ldg128_rlx(const void* p, uint32_t& r0, uint32_t& r1, uint32_t& r2, uint32_t& r3) {
  asm volatile("ld.relaxed.gpu.global.v4.u32 {%0, %1, %2, %3}, [%4];" : "=r"(r0), "=r"(r1), "=r"(r2), "=r"(r3) : "l"(p) : "memory");
}
__device__ __forceinline__ void ldg128_pred(const void* p, uint32_t* r, bool pr) {
  asm volatile("{\n.reg .pred p;\nsetp.ne.u32 p, %5, 0;\n@p ld.relaxed.gpu.global.v4.u32 {%0, %1, %2, %3}, [%4];\n}"
               : "+r"(r[0]), "+r"(r[1]), "+r"(r[2]), "+r"(r[3]) : "l"(p), "r"((uint32_t)pr) : "memory");
}
__device__ __forceinline__ void ldg64_rlx(const void* p, uint32_t& r0, uint32_t& r1) {
  asm volatile("ld.relaxed.gpu.global.v2.u32 {%0, %1}, [%2];" : "=r"(r0), "=r"(r1) : "l"(p) : "memory");
}
__device__ __forceinline__ void ldg128_nc(const void* p, uint32_t& r0, uint32_t& r1, uint32_t& r2, uint32_t& r3) {
  asm volatile("ld.global.nc.v4.u32 {%0, %1, %2, %3}, [%4];" : "=r"(r0), "=r"(r1), "=r"(r2), "=r"(r3) : "l"(p) : "memory");
}
__device__ __forceinline__ void stg128(uint4* p, uint32_t r0, uint32_t r1, uint32_t r2, uint32_t r3) {
  asm volatile("st.relaxed.gpu.global.v4.u32 [%0], {%1, %2, %3, %4};" ::"l"(p), "r"(r0), "r"(r1), "r"(r2), "r"(r3) : "memory");
}
__device__ __forceinline__ void stg128p(uint4* p, uint32_t r0, uint32_t r1, uint32_t r2, uint32_t r3, bool pr) {
  asm volatile("{\n.reg .pred p;\nsetp.ne.u32 p, %5, 0;\n@p st.relaxed.gpu.global.v4.u32 [%0], {%1, %2, %3, %4};\n}"
               ::"l"(p), "r"(r0), "r"(r1), "r"(r2), "r"(r3), "r"((uint32_t)pr) : "memory");
}
__device__ __forceinline__ uint32_t tagged(uint32_t v, uint32_t tag) { return (v & ~1u) | tag; }
__device__ __forceinline__ uint32_t stale(uint32_t acc, uint32_t v, uint32_t tag) {
  uint32_t r;
  asm("lop3.b32 %0, %1, %2, %3, 0xF6;" : "=r"(r) : "r"(acc), "r"(v), "r"(tag));
  return r;
}
template <int POS>
__device__ __forceinline__ void send_packets(uint4* dst, uint32_t (&G)[12], uint32_t s0, uint32_t& s1, uint32_t tag, int t,
                                             unsigned* flag) {
  G[0] = tagged(G[0], tag); G[4] = tagged(G[4], tag); G[8] = tagged(G[8], tag); s1 = tagged(s1, tag);
  if (POS == 0) { asm volatile("" : "+r"(G[0]), "+r"(G[11])); warp_red(flag, t & 31); }
  stg128(dst, G[0], G[1], G[2], G[3]);
  if (POS == 1) warp_red(flag, t & 31);
  stg128(dst + 128, G[4], G[5], G[6], G[7]);
  if (POS == 2) warp_red(flag, t & 31);
  stg128(dst + 256, G[8], G[9], G[10], G[11]);
  if (POS == 3) warp_red(flag, t & 31);
  asm volatile("st.relaxed.gpu.global.v2.u32 [%0], {%1, %2};" ::"l"(reinterpret_cast<uint2*>(dst + 384) - t), "r"(s0), "r"(s1) : "memory");
  if (POS == 4) warp_red(flag, t & 31);
}
__device__ __forceinline__ void to_slots(const uint32_t (&T)[7][2], uint32_t (&G)[12], uint32_t& s0, uint32_t& s1) {
#pragma unroll
  for (int i = 0; i < 12; i++) G[i] = T[i >> 1][i & 1];
  s0 = T[6][0];
  s1 = T[6][1];
}
#define G4(G, s) G[4 * (s)], G[4 * (s) + 1], G[4 * (s) + 2], G[4 * (s) + 3]
#define AFRAG(A, s) A[2 * (s)][0], A[2 * (s)][1], A[2 * (s) + 1][0], A[2 * (s) + 1][1]

__device__ __forceinline__ void quad_transpose(uint32_t* w, int lane) {
#pragma unroll
  for (int x = 1; x < 4; x <<= 1)
#pragma unroll
    for (int i = 0; i < 2; i++) {
      const int lo = x == 1 ? 2 * i : i;
      const uint32_t r = __shfl_xor_sync(0xffffffffu, (lane & x) ? w[lo] : w[lo + x], x);
      if (lane & x) w[lo] = r; else w[lo + x] = r;
    }
}
__device__ __forceinline__ float quad_sum(float v) {
  v += __shfl_xor_sync(0xffffffffu, v, 1);
  return v + __shfl_xor_sync(0xffffffffu, v, 2);
}
__device__ __forceinline__ float finish_rstd(float sq) { return rsqrtf((C7 ? sq : quad_sum(sq)) * (1.f / DM) + 1e-5f); }
__global__ void __cluster_dims__(2, 1, 1) __launch_bounds__(384, 1)
fused_kernel(const __grid_constant__ Maps maps, const char* __restrict__ x_g, const char* __restrict__ wo_g, const char* __restrict__ wg_g,
             const char* __restrict__ wu_g, const char* __restrict__ wd_g, __nv_bfloat16* __restrict__ outp) {
  extern __shared__ __align__(1024) char smem[];
  constexpr uint32_t sb = 1024;
  const uint32_t cta = smem_u32(smem) - sb;
  if (cta & 0xFFFFFFu) return;
  constexpr uint32_t bars = sb + BAR_OFF;
  constexpr uint32_t PB = sb + 65536;
  volatile unsigned* s_epoch = reinterpret_cast<volatile unsigned*>(smem + BAR_OFF + 8 * NBAR);
#define BAR(i) (cta + bars + 8u * (i))
#define SL(i) (sb + SLOT * (i))
#define ARRIVE(i, off) warp_arrive(BAR(i) + (off), lane)
#define INDICES()                                                                        \
  int bid, tid;                                                                          \
  asm volatile("mov.u32 %0, %%ctaid.x;\nmov.u32 %1, %%tid.x;" : "=r"(bid), "=r"(tid));   \
  bid = vbid(bid);                                                                       \
  const int lane = tid & 31, warp = tid >> 5, rank = bid & 1, j = JMAP(bid), rb = RBMAP(bid); (void)rank; (void)j
#define LOAD_TAG(tag)                                                                    \
  asm volatile("ld.shared.u32 %0, [%1];" : "=r"(tag) : "r"(BAR(NBAR)) : "memory"); \
  tag = (tag + 1) & 1

  if (threadIdx.x < 32) {
    if (elect()) {
      mbar_init(BAR(XF), 1);
      asm volatile("fence.mbarrier_init.release.cluster;" ::: "memory");
      tma2d(cta + sb, &maps.x, 0, 128 * RBMAP(VBID), BAR(XF));
      TS2(4);
#pragma unroll
      for (int i = 1; i < 7; i++) mbar_init(BAR(XF + i), 1);
      asm volatile("fence.mbarrier_init.release.cluster;" ::: "memory");
#pragma unroll
      for (int b = 1; b < 7; b++) tma2d(cta + sb + b * 16384, &maps.x, 64 * b, 128 * RBMAP(VBID), BAR(XF + b));
      TS2(2);
#pragma unroll
      for (int b = 0; b < 7; b++) mbar_expect(BAR(XF + b), 16384);
    }
    __syncwarp();
  }
  if (threadIdx.x == 224) TS2(0);
  if (threadIdx.x < 256) {
    asm volatile("barrier.cluster.arrive.relaxed.aligned;" ::: "memory");
    asm volatile("setmaxnreg.inc.sync.aligned.u32 %0;" ::"n"(RHI));
    bar_sync(0, 256);
    uint32_t HH[28][2], HP[28][2];
    {
    const int bid = VBID, tid = threadIdx.x;
    const int lane = tid & 31, warp = tid >> 5, j = JMAP(bid), rb = RBMAP(bid);
    const int wg = __shfl_sync(0xffffffffu, warp >> 2, 0);
    const int t128 = tid & 127;
    const int q = lane & 3;
    const int r0 = warp * 16;
    const int lrow = r0 + (lane & 7) + (lane & 8);
    const int lch = lane >> 4;
    const bool odd = j & 1;
    float rstd0, rstd1, mx0, mx1;
    uint32_t PQ[7][2], XR[8][2];
    unsigned ep;
    uint4* kvg;
    uint32_t W[16][4];
    const uint32_t c = lane & 7, nt = 2 * (warp & 3) + ((lane >> 3) & 1), mw = cta + SL(4) + wg * SLOT;
    auto LDW = [&]() {
      const uint32_t u = c < 6 ? 1024u : 0u;
      TSY(wg, 27);
      mbar_wait(BAR(RS));
      TSY(wg, 28);
#pragma unroll
      for (int pp = 0; pp < 2; pp++) {
        const uint32_t rho = 28 * lch + 14 * pp + c, src = (nt == 7 || !odd) ? nt : nt == 6 ? 0 : nt + 1;
        const uint32_t a = mw + rho * 128 + (((src ^ rho) & 7) << 4);
#pragma unroll
        for (int i = 0; i < 8; i++) {
          const int k = i & 3;
          ldsm4t(a + (k == 0 ? 0 : k == 1 ? 7 * u : k == 2 ? 7168 - 6 * u : 7168 + u) + (i >> 2) * BLK, G4(W[(i >> 2) * 8 + pp * 4 + k], 0));
        }
      }
    };
    TS(wg, 0);
    {
      uint32_t A[56][2];
      {
        float cs[2][2] = {}, g[2][2] = {}, cm[2][4] = {};
        auto squares = [&](int b) {
#pragma unroll
          for (int h = 0; h < 2; h++) {
            uint32_t d[8];
#pragma unroll
            for (int t = 0; t < 8; t++) d[t] = A[8 * b + t][h];
            const uint32_t t = add2(fma2(d[0], fma2(d[1], fma2(d[2], fma2(d[3], 0x80008000u)))),
                                    fma2(d[4], fma2(d[5], fma2(d[6], fma2(d[7], 0x80008000u)))));
            g[h][0] += bf_lo(t); g[h][1] += bf_hi(t);
          }
          asm volatile("" : "+f"(g[0][0]), "+f"(g[0][1]), "+f"(g[1][0]), "+f"(g[1][1]));
        };
#define CENTER(t0, t1) _Pragma("unroll") for (int t_ = 0; t_ < 56; t_++) if (t_ >= (t0) && t_ < (t1)) { A[t_][0] = sub2v(A[t_][0], mb0); A[t_][1] = sub2v(A[t_][1], mb1); }
#pragma unroll
        for (int b = 0; b < 7; b++) {
          if (b == 6) asm volatile("barrier.cluster.wait.aligned;" ::: "memory");
          mbar_wait(BAR(XF + b));
          if (b == 0) TSA(wg, 23);
          if (b == 6) TSA(wg, 27);
#pragma unroll
          for (int kk = 0; kk < 4; kk++)
            ldsm4(cta + sb + b * 16384 + lrow * 128 + (((2 * kk + lch) ^ (lane & 7)) << 4), AFRAG(A, 4 * b + kk));
          if (DLY && b) squares(b - 1);
          if (K8) {
#pragma unroll
            for (int s = 4 * b; s < 4 * b + 4; s++) mma16(cm[s & 1], AFRAG(A, s), 0x3F803F80u, 0x3F803F80u);
          } else {
#pragma unroll
            for (int h = 0; h < 2; h++) {
              const uint32_t t = add2(add2(add2(A[8 * b][h], A[8 * b + 1][h]), add2(A[8 * b + 2][h], A[8 * b + 3][h])),
                                      add2(add2(A[8 * b + 4][h], A[8 * b + 5][h]), add2(A[8 * b + 6][h], A[8 * b + 7][h])));
              cs[h][0] += bf_lo(t); cs[h][1] += bf_hi(t);
            }
          }
          if (!DLY && b < 6) squares(b);
        }
        mx0 = (K8 ? cm[0][0] + cm[1][0] : quad_sum(cs[0][0] + cs[0][1])) * (1.f / DM);
        mx1 = (K8 ? cm[0][2] + cm[1][2] : quad_sum(cs[1][0] + cs[1][1])) * (1.f / DM);
        const uint32_t mb0 = pack2(mx0, mx0), mb1 = pack2(mx1, mx1);
        float ka[28], va[28];
#define KS(s0, s1) _Pragma("unroll") for (int s = s0; s < s1; s++) wgmma_rs_n56<H128>(ka, AFRAG(A, s), dlo(SL(4) + s * 2048, 0), s > 0)
        CENTER(0, 6);
        mbar_wait(BAR(WS));
        wg_fence();
        TS(wg, 1);
        KS(0, 3);
        CENTER(6, 14);
        wg_fence();
        KS(3, 7);
#pragma unroll
        for (int g = 0; g < 4; g++) {
          const int T = 7 * j + (g < 3 ? 2 * g + lch + odd : odd ? 0 : 6);
          const uint32_t a = cta + sb + (T >> 3) * 16384 + lrow * 128 + (((T ^ lane) & 7) << 4);
          if (g < 3) ldsm4(a, AFRAG(XR, g)); else ldsm2(a, XR[6][0], XR[6][1]);
        }
        CENTER(14, 28);
        asm volatile("" ::"r"(XR[0][0]), "r"(XR[2][0]), "r"(XR[4][0]), "r"(XR[6][0]) : "memory");
        warp_arrive2(BAR(XE), lane);
        mbar_wait(BAR(WS + 1));
        wg_fence();
        KS(7, 14);
        CENTER(28, 42);
        mbar_wait(BAR(WS + 2));
        wg_fence();
        KS(14, 21);
        squares(6);
        CENTER(42, 56);
        mbar_wait(BAR(WS + 3));
        wg_fence();
        KS(21, 28);
        wg_commit();
        {
          float v0 = quad_sum(g[0][0] + g[0][1]) * (1.f / DM) - mx0 * mx0, v1 = quad_sum(g[1][0] + g[1][1]) * (1.f / DM) - mx1 * mx1;
          if (__builtin_expect(__any_sync(0xffffffffu, mx0 * mx0 > 4.f * v0 || mx1 * mx1 > 4.f * v1), 0)) {
            const uint32_t* xr = reinterpret_cast<const uint32_t*>(x_g) + (rb * 128 + r0 + (lane >> 2)) * (DM / 2) + q;
            v0 = v1 = 0.f;
#pragma unroll 1
            for (int t = 0; t < DM / 2; t += 4) {
              const uint32_t a = __ldg(xr + t), b = __ldg(xr + 8 * (DM / 2) + t);
              const float a0 = bf_lo(a) - mx0, a1 = bf_hi(a) - mx0, b0 = bf_lo(b) - mx1, b1 = bf_hi(b) - mx1;
              v0 = fmaf(a0, a0, fmaf(a1, a1, v0));
              v1 = fmaf(b0, b0, fmaf(b1, b1, v1));
            }
            v0 = quad_sum(v0) * (1.f / DM);
            v1 = quad_sum(v1) * (1.f / DM);
          }
          rstd0 = rsqrtf(v0 + 1e-5f);
          rstd1 = rsqrtf(v1 + 1e-5f);
        }
        const float e0 = rstd0 * 1.4426950408889634f, e1 = rstd1 * 1.4426950408889634f;
        mbar_wait(BAR(EP));
        ep = *s_epoch;
        kvg = &g_kv[((ep & 1) * 8 + j) * KVP + (r0 & 63) * 4 + q * 8 + (lane >> 2)];
#pragma unroll
        for (int b = 0; b < 4; b++) {
          mbar_wait(BAR(WV + b));
          wg_fence();
#pragma unroll
          for (int s = 7 * b; s < 7 * b + 7; s++) wgmma_rs_n56<H128>(va, AFRAG(A, s), dlo(SL(6) + s * 2048, 0), s > 0);
          if (b == 0 || b == 3) wg_commit();
          if (b == 0) {
            wg_wait<1>();
            TSA(wg, 30);
            warp_arrive2(BAR(KE), lane);
          }
          uint32_t P[2][2];
#pragma unroll
          for (int i = 2 * b; i < 2 * b + 2; i++) {
            if (i < 7) {
              asm volatile("" : "+f"(ka[4 * i]), "+f"(ka[4 * i + 1]), "+f"(ka[4 * i + 2]), "+f"(ka[4 * i + 3]));
              P[i & 1][0] = pack2(phi(ka[4 * i], rstd0, e0), phi(ka[4 * i + 1], rstd0, e0));
              P[i & 1][1] = pack2(phi(ka[4 * i + 2], rstd1, e1), phi(ka[4 * i + 3], rstd1, e1));
            } else {
              P[1][0] = P[1][1] = 0u;
            }
          }
          stsm4(cta + PB + lrow * 128 + (((2 * b + lch) ^ (lane & 7)) << 4), AFRAG(P, 0));
        }
        wg_wait<0>();
        TS(wg, 2);
        uint32_t V[8][2];
#pragma unroll
        for (int i = 0; i < 7; i++) {
          V[i][0] = pack2(va[4 * i] * rstd0, va[4 * i + 1] * rstd0);
          V[i][1] = pack2(va[4 * i + 2] * rstd1, va[4 * i + 3] * rstd1);
        }
        V[7][0] = V[7][1] = 0x00003F80u;
#pragma unroll
        for (int g = 0; g < 4; g++) stsm4(cta + PB + 16384 + lrow * 128 + (((2 * g + lch) ^ (lane & 7)) << 4), AFRAG(V, g));
        fence_async_smem();
      }
      if (wg == 0) {
        bar_arrive(1, 256);
      } else {
        bar_sync(1, 256);
        TS(wg, 29);
        float kv[32];
        wg_fence();
#pragma unroll
        for (int s = 0; s < 8; s++)
          wgmma_ss_n64<H128>(kv, dlo(PB + s * 2048, 0), dlo(PB + 16384 + s * 2048, 0), s > 0);
        wg_commit();
        if (B2 == 0) bar_arrive(2, 256);
        float2* const zg = &g_z[ep & 1][j][(r0 & 63) + (lane >> 2) + 8 * q];
        wg_wait<0>();
        asm volatile("{\n.reg .pred p;\nsetp.lt.u32 p, %3, 2;\n@p red.relaxed.gpu.global.add.v2.f32 [%0], {%1, %2};\n}"
                     ::"l"(zg), "f"(q ? kv[30] : kv[28]), "f"(1.f), "r"(q) : "memory");
        if (B2 == 1) bar_arrive(2, 256);
        if (KMC == 2) warp_arrive2(BAR(KM), lane); else if (!KMC) pred_arrive(BAR(KM), lane == 0);
        TS(wg, 26);
#pragma unroll
        for (int hh = 0; hh < 2; hh++) {
          const int d = (r0 & 63) + (lane >> 2) + 8 * hh;
          const bool h0 = d < 28;
          const uint32_t x = __shfl_sync(0xffffffffu, pack2(kv[12 + 2 * hh], kv[13 + 2 * hh]), (lane & 29) | (h0 ? 0 : 2));
          uint32_t a[3];
#pragma unroll
          for (int i = 0; i < 3; i++) {
            const int y = 4 * i + 2 * hh;
            a[i] = pack2(h0 ? kv[y] : kv[16 + y], h0 ? kv[y + 1] : kv[17 + y]);
          }
          red8(kvg + 32 * hh, a[0], a[1], a[2], __byte_perm(x, 0x3F80u, q < 2 ? 0x5410 : 0x3254), d < 56);
          if (B2 == 2 + hh) bar_arrive(2, 256);
        }
        if (KMC == 3) warp_arrive2(BAR(KM), lane);
      }
      TS(wg, 3);
      {
        asm volatile("{\n.reg .pred p;\nsetp.eq.u32 p, %0, 0;\n@p bar.sync 2, 256;\n@!p bar.sync 6, 256;\n}" ::"r"(wg) : "memory");
        float qa[28];
        mbar_wait(BAR(WQ0));
        TSA(wg, 25);
        wg_fence();
#pragma unroll
        for (int s = 0; s < 14; s++) wgmma_rs_n56<H128>(qa, AFRAG(A, s), dlo(SL(0) + s * 2048, 0), s > 0);
        mbar_wait(BAR(WQ1));
        TSA(wg, 28);
        wg_fence();
#pragma unroll
        for (int s = 14; s < 28; s++) {
          wgmma_rs_n56<H128>(qa, AFRAG(A, s), dlo(SL(0) + s * 2048, 0), 1);
          if (s == QP) pred_bar_arrive(6, wg == 0);
        }
        wg_commit();
        const float e0 = rstd0 * 1.4426950408889634f, e1 = rstd1 * 1.4426950408889634f;
        wg_wait<0>();
        warp_arrive(BAR(QE), lane);
        if (EL == 1) LDW();
#pragma unroll
        for (int i = 0; i < 28; i++) qa[i] = (i & 2) ? phi(qa[i], rstd1, e1) : phi(qa[i], rstd0, e0);
#pragma unroll
        for (int i = 0; i < 14; i++) {
          PQ[i >> 1][i & 1] = pack2(qa[2 * i], qa[2 * i + 1]);
          asm volatile("" : "+r"(PQ[i >> 1][i & 1]));
        }
        TS(wg, 4);
        if (EL == 2) LDW();
        mbar_wait(BAR(ZF));
        uint32_t zb[8];
        lds128(cta + sb + Z_OFF + 16 * (lane & 7), G4(zb, 0));
        lds128(cta + sb + Z_OFF + 128 + 16 * (lane & 7), G4(zb, 1));
        float dn[2][4] = {{1e-6f, 1e-6f, 1e-6f, 1e-6f}, {}};
#pragma unroll
        for (int s = 0; s < 4; s++)
          mma16(dn[s & 1], PQ[2 * s][0], PQ[2 * s][1], PQ[s < 3 ? 2 * s + 1 : 6][0], PQ[s < 3 ? 2 * s + 1 : 6][1], zb[2 * s], zb[2 * s + 1]);
#pragma unroll
        for (int hh = 0; hh < 2; hh++) {
          const float ra = rcpf(dn[0][2 * hh] + dn[1][2 * hh]), rb_ = rcpf(dn[0][2 * hh + 1] + dn[1][2 * hh + 1]);
          const uint32_t pa = pack2(ra, ra), pb = pack2(rb_, rb_);
#pragma unroll
          for (int i = 0; i < 7; i++) PQ[i][hh] = mul2(PQ[i][hh], (i < 3 || (i == 3 && q < 2)) ? pa : pb);
        }
      }
    }
    const uint32_t tag = (ep + 1) & 1;
    uint4* const xb = &g_x[(rb * 16 + wg) * (HB / 16) + t128];
    unsigned* const flag = &g_flag[rb * 32 + j * 2 + wg];
    const uint32_t u0 = ((j >> 1) & 1) * 896u, u1 = 896u - u0;
    const uint32_t b0 = (j & 1) * 512u, b1 = 512u - b0;
    const uint32_t ko[4] = {u0 + b0, u0 + b1, u1 + b0, u1 + b1};
    uint32_t A[8][12], ST[4][4];
    uint32_t E[2][4], S0, S1;
    to_slots(PQ, A[0], S0, S1);
    send_packets<FQ>(xb + (j * 2) * (HB / 16), A[0], S0, S1, tag, t128, flag);
    TS(wg, 6);
    {
      const uint32_t ks = cta + SL(6) + wg * BLK + t128 * 16;
      const uint32_t kb = dlo(SL(6), 128) + wg * (BLK >> 4);
      uint32_t P[28][2];
      float m[3][2][16];
      if (!EL) LDW();
      auto mma = [&](int i) {
#pragma unroll
        for (int n = 0; n < 4; n++) {
          const int k = MO ? (n >> 1) + 2 * (n & 1) : n;
          wgmma_rs_n32<HK>(m[i % 3][k >> 1], G4(W[4 * i + k], 0), kb + i * 224 + (k >> 1) * 96 + (k & 1) * 16, k & 1);
        }
        wg_commit();
      };
      auto pack = [&](int i) {
        const float* d0 = m[i % 3][0];
        const float* d1 = m[i % 3][1];
#pragma unroll
        for (int n = 0; n < 14; n++) {
          const int t = n >> 1, pos = 7 * i + ((i & 1) ? (t + 1) % 7 : t);
          P[pos][n & 1] = t < 3 ? pack2(d0[2 * n], d0[2 * n + 1]) : t > 3 ? pack2(d1[2 * n - 12], d1[2 * n - 11])
                          : pack2(q < 2 ? d0[2 * n] : d1[2 * n - 12], q < 2 ? d0[2 * n + 1] : d1[2 * n - 11]);
        }
      };
      auto store = [&](int g0, int g1) {
#pragma unroll
        for (int g = g0; g < g1; g++) stsm4t(mw + lch * 1024 + c * 128 + ((nt ^ c) << 4) + g * 2048, AFRAG(P, g));
      };
      TSY(wg, 30);
      mbar_wait(BAR(KF) + 8u * wg);
      TSM(11);
      const uint32_t cmask = lch ? 0xFFFFu : 0xFFFF0000u;
#pragma unroll 1
      for (uint32_t it = 0;; it++) {
        uint32_t cn = 0, bad, v[7];
#pragma unroll
        for (int i = 0; i < 7; i++) asm volatile("ld.shared.u32 %0, [%1];" : "=r"(v[i]) : "r"(ks + i * 2048 + 12) : "memory");
        if (DC) {
          wg_fence();
          mma(0);
          mma(1);
          mma(2);
          if (DC >= 3) {
            wg_wait<2>();
            pack(0);
            wg_fence();
            mma(3);
            wg_wait<2>();
            pack(1);
            if (DC == 3) {
              wg_wait<1>();
              pack(2);
              wg_wait<0>();
              pack(3);
            }
#pragma unroll
            for (int i = 0; i < (DC == 3 ? 28 : 14); i++) asm volatile("" : "+r"(P[i][0]), "+r"(P[i][1]));
          }
          if (DC >= 2) mbar_wait(BAR(KF) + 8u * wg);
        }
#pragma unroll
        for (int i = 0; i < 7; i++) cn |= v[i];
        asm volatile("{\n.reg .pred p, q;\nsetp.ne.u32 q, %2, 0;\nbar.red.or.pred p, %1, 128, q;\nselp.u32 %0, 1, 0, p;\n}"
                     : "=r"(bad) : "r"(8 + wg), "r"(it ? 0u : cn & cmask) : "memory");
        if (__builtin_expect(!__any_sync(0xffffffffu, bad), 1)) break;
        if (DC) { wg_wait<0>(); bar_sync(8 + wg, 128); }
        const uint4* kvp = &g_kv[((ep & 1) * 8 + 4 * ((j >> 2) ^ wg)) * KVP + t128];
#pragma unroll 1
        for (int n = 0, e = 0; n < 4 * KVP; n += 128) {
          uint32_t v[4];
          do { ldg128_rlx(kvp + n, G4(v, 0)); } while ((v[3] & cmask) && ++e < SPIN_LIMIT);
          sts128(ks + n * 16, G4(v, 0));
        }
        COUNT_FALLBACK(0);
        fence_async_smem();
        bar_sync(8 + wg, 128);
        if (!DC) break;
      }
      TS(wg, 5);
      if (!DC) {
        wg_fence();
        mma(0);
        mma(1);
        mma(2);
      }
      TSM(16);
      wg_wait<2>();
      TSM(17);
      pack(0);
      wg_fence();
      mma(3);
      TSB(wg, 23);
      store(0, 3);
      wg_wait<2>();
      pack(1);
      store(3, 7);
      wg_wait<1>();
      pack(2);
      store(7, 10);
      TSM(18);
      wg_wait<0>();
      TSB(wg, 25);
      pack(3);
      store(10, 14);
      TSM(19);
      fence_async_smem();
      warp_arrive(BAR(MR) + 8u * wg, lane);
      warp_arrive2(BAR(KD), lane);
    }
    TS(wg, 20);
#define RECV_LD(r, GB)                                                                                     \
  do {                                                                                                     \
    lds128(xs + (r) * HB, G4(A[r], 0));                                                                    \
    lds128(xs + (r) * HB + 2048, G4(A[r], 1));                                                             \
    lds128(xs + (r) * HB + 4096, G4(A[r], 2));                                                             \
    if (C7 || !(GB)) lds64(xe + (r) * HB, E[(r) & 1][0], E[(r) & 1][1]);                                   \
    else lds128(xs + (r) * HB + 6144, G4(E[(r) & 1], 0));                                                  \
    if (C7 && (GB)) lds64(xq + (r) * HB, E[(r) & 1][2], E[(r) & 1][3]);                                    \
  } while (0)
#define BADP(r, x, GB) stale(stale(stale(stale(C7 && (GB) ? stale(x, E[(r) & 1][1], tag) : x, A[r][0], tag), A[r][4], tag), A[r][8], tag), E[(r) & 1][(GB) ? 3 : 1], tag)
#define RECV_CHECK(g, GB)                                                                                  \
  do {                                                                                                     \
    if (SLOWP) bd = BADP(2 * g + 1, g ? BADP(2 * g, bd, GB) : 0u, GB);                                             \
    if (GB) {                                                                                              \
      ss0 += __uint_as_float(E[1][2]); ss1 += __uint_as_float(E[1][3]);                                    \
      if (g) { ss0 += __uint_as_float(E[0][2]); ss1 += __uint_as_float(E[0][3]); }                         \
    }                                                                                                      \
    ST[g][0] = odd ? E[1][0] : g ? E[0][0] : S0; ST[g][1] = odd ? E[1][1] : g ? E[0][1] : S1;              \
    ST[g][2] = odd ? g ? E[0][0] : S0 : E[1][0]; ST[g][3] = odd ? g ? E[0][1] : S1 : E[1][1];              \
    asm volatile("" : "+r"(ST[g][0]), "+r"(ST[g][1]), "+r"(ST[g][2]), "+r"(ST[g][3]));                     \
  } while (0)
#define ANY_BAD()                                                                                          \
  if (SLOWP) asm volatile("{\n.reg .pred p, q;\nsetp.ne.u32 q, %2, 0;\nbar.red.or.pred p, %1, 128, q;\nselp.u32 %0, 1, 0, p;\n}"   \
               : "=r"(bd) : "r"(8 + wg), "r"(it ? 0u : bd & 1u) : "memory")
#define REPAIR(GB)                                                                                         \
  _Pragma("unroll 1") for (int n = 1, e = 0; n < 8; n++) {                                                 \
                                                                           \
    const int o[5] = {0, 128, 256, 384 + (t128 >> 1) - t128, 448 + (t128 >> 3) - t128};                    \
    uint32_t v[5][4], x;                                                                                   \
    do {                                                                                                   \
      x = 0;                                                                                               \
      _Pragma("unroll") for (int k = 0; k < 4 + (GB) / 256; k++)                                           \
          ldg128_rlx(xb + ((GB) + 2 * (j ^ n)) * (HB / 16) + o[k], G4(v[k], 0));                           \
      _Pragma("unroll") for (int k = 0; k < 4 + (GB) / 256; k++)                                           \
          x = k < 3 ? stale(x, v[k][0], tag) : stale(stale(x, v[k][1], tag), v[k][3], tag);                \
    } while ((x & 1) && ++e < SPIN_LIMIT);                                                                 \
    _Pragma("unroll") for (int k = 0; k < 4 + (GB) / 256; k++) sts128(xs + n * HB + o[k] * 16, G4(v[k], 0)); \
  }                                                                                                        \
  fence_async_smem();                                                                                      \
  COUNT_FALLBACK(1 + (GB) / 256);                                                                          \
  __syncwarp()
#define VARIANT()                                                                                          \
  const uint32_t v0 = u0 + (it >> 16), v1 = u1 + (it >> 16), kv_[4] = {v0 + b0, v0 + b1, v1 + b0, v1 + b1}
#define KOFF(r) ko[(r) & 3]
#define SOFF(r) ((((r) & 2) ? u1 : u0) + 384u)
#define REP4(M) M(0) M(1) M(2) M(3)
    uint32_t xs = cta + sb - HB + wg * (7 * HB) + t128 * 16;
    uint32_t xe = xs + 6144 - t128 * 8, xq = 0;
    float ss0, ss1;
    {
      float ha[32];
#define MMA_BLOCK(W, acc, r, base, sh, first)                                                              \
  _Pragma("unroll") for (int s = 0; s < 3; s++)                                                            \
      W(acc, G4(A[r], s), base + (kv_[(r) & 3] >> sh) + s * (128 >> sh), r + s > 0 ? 1 : first)
#define MMA_GROUP(W, acc, g, base, sh, i0, i1)                                                             \
  _Pragma("unroll") for (int i = (i0); i < (i1); i++) {                                                    \
    if (i < 6) W(acc, G4(A[2 * g + i / 3], i % 3), base + (kv_[(2 * g + i / 3) & 3] >> sh) + (i % 3) * (128 >> sh), 1); \
    else W(acc, G4(ST[g], 0), base + (((g & 1) ? v1 : v0) >> sh) + (384u >> sh), 1);                       \
  }
#define RECV_NEXT(g, FB, f)                                                                                \
  if (g < 3) { if (!(f)) mbar_wait(BAR(FB + g + 1) + 32u * wg); RECV_LD(g < 3 ? 2 * g + 2 : 1, FB - OF); RECV_LD(g < 3 ? 2 * g + 3 : 1, FB - OF); }
#define RELEASE()                                                                                          \
  ANY_BAD();                                                                                               \
  pred_arrive(BAR(WE) + 8u * wg, (lane | bd) == 0);                                                        \
  if (W0) { wg_wait<1>(); pred_arrive(BAR(WOE0), (lane | bd) == 0); }
#define WO_RECV(g)                                                                                         \
  {                                                                                                        \
    if (CO & 1) mbar_wait(BAR(OF + (g < 3 ? g + 1 : 3)) + 32u * wg);                                       \
    RECV_CHECK(g, 0);                                                                                      \
    if (g == 0) TS(wg, 7);                                                                                 \
    if (g == 3) TS(wg, 21);                                                                                \
    if (g == 1 || g == 2) TSH(8 + g);                                                                      \
    if (g == 3) { RELEASE(); TSH(11); }                                                                    \
    RECV_NEXT(g, OF, CO & 1);                                                                                 \
  }
#define WO_MMA(g)                                                                                          \
  {                                                                                                        \
    if (g == 2) mbar_wait(BAR(MR + g / 2));                                                                \
    if (g == 0 && HP0 >= 0)                                                                                \
      asm volatile("{\n.reg .pred p;\nsetp.gt.u32 p, %0, %1;\n@p bar.sync 3, 256;\n}" ::"r"(wg), "r"(it) : "memory"); \
    constexpr uint32_t base = dlo(SL(g < 2 ? 4 : 5), 0);                                                   \
    wg_fence();                                                                                            \
    MMA_GROUP(wgmma_rs_n64<H128>, ha, g, base, 0, g ? 0 : 3, 7);                                           \
    if (g == 3 || (W0 && g)) wg_commit();                                                                  \
    if (g == HP0) pred_bar_arrive(3, (wg | it) == 0);                                                      \
  }
#define AHEAD(R, M, n)                                                                                     \
  R(0) if (n == 0) M(0)                                                                                    \
  R(1) if (n == 0) M(1) if (n == 1) M(0)                                                                   \
  R(2) if (n == 0) M(2) if (n == 1) M(1) if (n == 2) M(0) if (n == 4) { M(0) M(1) }                        \
  R(3) if (n == 3) M(0) if (n == 2 || n == 3) M(1) if (n) M(2) M(3)
      if (OWN) mbar_wait(BAR(MR));
      TSH(16);
#pragma unroll 1
      for (uint32_t it = 0;; it++) {
        uint32_t bd = 0;
        VARIANT();
        if (TOPR && it) { REPAIR(0); }
        if (!OWN) {
          mbar_wait(BAR(OF) + 32u * wg);
          RECV_LD(1, 0);
        }
#pragma unroll
        for (int i = 0; i < 7; i++) asm volatile("" : "+r"(XR[i][0]), "+r"(XR[i][1]));
#pragma unroll
        for (int i = 0; i < 14; i++) { ha[2 * i] = bf_lo(XR[i >> 1][i & 1]); ha[2 * i + 1] = bf_hi(XR[i >> 1][i & 1]); }
        asm volatile("mov.b32 %0, %2;\nmov.b32 %1, %3;" : "=&f"(ha[28]), "=f"(ha[30]) : "f"(mx0), "f"(mx1));
        ha[29] = ha[31] = 0.f;
#pragma unroll
        for (int i = 0; i < 32; i++) asm volatile("" : "+f"(ha[i]));
        if (OWN) {
          wg_fence();
          MMA_GROUP(wgmma_rs_n64<H128>, ha, 0, dlo(SL(4), 0), 0, 0, 3);
          TSH(17);
          mbar_wait(BAR(OF) + 32u * wg);
          TSH(18);
          RECV_LD(1, 0);
        }
        AHEAD(WO_RECV, WO_MMA, AH)
        TSH(12);
        wg_wait<0>();
        TSH(13);
        if (__builtin_expect(!__any_sync(0xffffffffu, bd), 1)) break;
        if (!TOPR) { REPAIR(0); }
      }
      ARRIVE(WOE1, 0);
      const uint32_t mm[2] = {pack2(ha[28] + ha[29], ha[28] + ha[29]), pack2(ha[30] + ha[31], ha[30] + ha[31])};
      uint32_t C[7][2];
#pragma unroll
      for (int i = 0; i < 14; i++) C[i >> 1][i & 1] = sub2(pack2(ha[2 * i], ha[2 * i + 1]), mm[i & 1]);
      to_slots(C, A[0], S0, S1);
      TSH(14);
      send_packets<FP>(xb + (256 + j * 2) * (HB / 16), A[0], S0, S1, tag, t128, flag + 512);
      mbar_wait(BAR(MR));
      {
        uint32_t t[2];
#pragma unroll
        for (int h = 0; h < 2; h++)
          t[h] = add2(fma2(C[0][h], fma2(C[1][h], fma2(C[2][h], fma2(C[3][h], 0x80008000u)))),
                      fma2(C[4][h], fma2(C[5][h], fma2(C[6][h], 0x80008000u))));
        ss0 = bf_lo(t[0]) + bf_hi(t[0]);
        ss1 = bf_lo(t[1]) + bf_hi(t[1]);
      }
      if (C7) {
        ss0 = quad_sum(ss0);
        ss1 = quad_sum(ss1);
        asm volatile("{\n.reg .pred p;\nsetp.eq.u32 p, %3, 0;\n@p st.relaxed.gpu.global.v2.u32 [%0], {%1, %2};\n}"
                     ::"l"(reinterpret_cast<char*>(xb + (256 + j * 2) * (HB / 16) + 448) - 14 * t128), "r"(__float_as_uint(ss0)),
                       "r"(tagged(__float_as_uint(ss1), tag)), "r"(q) : "memory");
      }
      if (FP == 5) warp_red(flag + 512, lane);
      asm volatile("{\n.reg .pred p;\nsetp.eq.s32 p, %3, %4;\n@p st.shared.v2.f32 [%0], {%1, %2};\n}"
                   ::"r"(cta + sb + MST_OFF + lane * 8), "f"(bf_lo(mm[0])), "f"(bf_lo(mm[1])), "r"(warp), "r"(j) : "memory");
    }
    TS(wg, 8);
    float ns0, ns1;
    auto glu = [&](float g, float u, float ns, float rs) {
      if (TH) { const float w = u * ns; return fmaf(tanhf_(g * ns), w, w); }
      return rcpf(1.f + ex2f(g * ns)) * (u * rs);
    };
#define PUBLISH(H, i0, n)                                                                                  \
  {                                                                                                        \
    int t2;                                                                                                \
    uint32_t tg;                                                                                           \
    asm volatile("mov.u32 %0, %%tid.x;" : "=r"(t2));                                                       \
    LOAD_TAG(tg);                                                                                          \
    uint4* sp = &g_h[bid * (14 * 256) + (i0) * 256 + t2];                                                  \
    _Pragma("unroll") for (int i = 0; i < n; i++)                                                          \
        stg128(sp + 256 * i, tagged((H)[2 * i][0], tg), (H)[2 * i][1], (H)[2 * i + 1][0], (H)[2 * i + 1][1]); \
  }
#define GU_ROW(r, base)                                                                                    \
  _Pragma("unroll") for (int s = 0; s < 3; s++) wgmma_rs_n128<H128>(acc, G4(A[r], s), base + KOFF(r) + s * 128, r + s > 0); \
  if (r & 1) wgmma_rs_n128<H128>(acc, G4(ST[r >> 1], 0), base + SOFF(r), 1)
    float acc[64];
    {
#define GU_RECV(g)                                                                                         \
  {                                                                                                        \
    if (CO & 2) mbar_wait(BAR(HF + (g < 3 ? g + 1 : 3)) + 32u * wg);                                       \
    RECV_CHECK(g, 256);                                                                                    \
    if (g == 0) TS(wg, 9);                                                                                 \
    if (g == 2) TS(wg, 22);                                                                                \
    if (g == 3) { ANY_BAD(); pred_arrive(BAR(HE) + 8u * wg, (lane | bd) == 0); TSG(1); }                   \
    RECV_NEXT(g, HF, CO & 2);                                                                                 \
  }
#define GU_MMA(g)                                                                                          \
  {                                                                                                        \
    if (g == 0 && T0) asm volatile("{\n.reg .pred p;\nsetp.gt.u32 p, %0, %1;\n@p bar.sync 4, 256;\n}" ::"r"(wg), "r"(it) : "memory"); \
    constexpr uint32_t base = dlo(SL(g < 2 ? 0 : 6), SLOT);                                                \
    wg_fence();                                                                                            \
    MMA_GROUP(wgmma_rs_n128<H128>, acc, g, base, 0, g ? 0 : 3, 7);                                         \
    if (T0 && g == T0 - 1) pred_bar_arrive(4, (wg | it) == 0);                                             \
    if (NT > 1 && g == NT - 2) pred_bar_arrive(7, wg > it);                                                \
  }
      xs += (wg ^ 1) * (4 * SLOT);
      xe = xs + 6144 - t128 * 8;
      xq = xs + 7168 - t128 * 16 + (t128 >> 2) * 8;
      mbar_wait(BAR(GUF + 1));
      mbar_wait(BAR(GUF));
      const float so0 = ss0, so1 = ss1;
#pragma unroll 1
      for (uint32_t it = 0;; it++) {
        uint32_t bd = 0;
        VARIANT();
        if (TOPR && it) { REPAIR(256); }
        ss0 = so0; ss1 = so1;
        wg_fence();
        MMA_BLOCK(wgmma_rs_n128<H128>, acc, 0, dlo(SL(0), SLOT), 0, 0);
        mbar_wait(BAR(HF) + 32u * wg);
        RECV_LD(1, 1);
        AHEAD(GU_RECV, GU_MMA, AC)
        wg_commit();
        if (NT == 0) pred_bar_arrive(7, wg > bd);
        TS(wg, 10);
        rstd0 = finish_rstd(ss0);
        rstd1 = finish_rstd(ss1);
        ns0 = (TH ? 0.5f : -1.4426950408889634f) * rstd0; ns1 = (TH ? 0.5f : -1.4426950408889634f) * rstd1;
        wg_wait<0>();
        if (__builtin_expect(!__any_sync(0xffffffffu, bd), 1)) break;
      }
    }
    ARRIVE(GUE, 0);
    TS(wg, 11);
#define GLU_CHUNK(o, c)                                                                                    \
  _Pragma("unroll") for (int i = 0; i < 8; i++) {                                                          \
    HH[o + i][0] = pack2(glu(acc[4 * i], acc[32 + 4 * i], ns0, rstd0), glu(acc[4 * i + 1], acc[32 + 4 * i + 1], ns0, rstd0)); \
    HH[o + i][1] = pack2(glu(acc[4 * i + 2], acc[32 + 4 * i + 2], ns1, rstd1), glu(acc[4 * i + 3], acc[32 + 4 * i + 3], ns1, rstd1)); \
  }                                                                                                        \
  PUBLISH(HH + o, 2 + 4 * (c), 4)
#define UNPARK()                                                                                           \
  {                                                                                                        \
    int t2;                                                                                                \
    asm volatile("mov.u32 %0, %%tid.x;" : "=r"(t2));                                                       \
    const uint4* sp = &g_h[bid * (14 * 256) + t2];                                                         \
    if (!EU) _Pragma("unroll") for (int i = PEEL ? 5 : 9; i >= 0; i--) ldg128_rlx(sp + 256 * i, AFRAG(HH, i));                 \
    sp = &g_h[(bid ^ 16) * (14 * 256) + t2];                                                               \
    _Pragma("unroll") for (int i = EU ? 8 : 0; i < NH; i++) ldg128_rlx(sp + 256 * i, AFRAG(HP, i));                 \
  }
    {
#pragma unroll 1
      for (int c = 1;; c++) {
        const uint32_t sa = c == 1 ? dlo(SL(2), SLOT) : dlo(SL(4), SLOT), sbb = c == 1 ? dlo(SL(6), SLOT) : dlo(SL(0), SLOT);
        GLU_CHUNK(12, c - 1);
        if (c == 1) {
          TS(wg, 12);
          float hc[32];
          if (NT != 1) turn_wait(wg);
          else asm volatile("{\n.reg .pred p;\nsetp.ne.u32 p, %0, 0;\n@p bar.sync 4, 256;\n}" ::"r"(wg) : "memory");
          mbar_wait(BAR(HAF));
          TSG(2);
          wg_fence();
#pragma unroll
          for (int r = 0; r < 8; r++) {
            constexpr uint32_t h0 = dlo(SL(4), BLK), h1 = dlo(SL(5), BLK);
            if (r == 4) mbar_wait(BAR(HBF));
#pragma unroll
            for (int s = 0; s < 3; s++) wgmma_rs_n64<H64>(hc, G4(A[r], s), (r < 4 ? h0 : h1) + (KOFF(r) >> 1) + s * 64, r + s > 0);
            if (r & 1) wgmma_rs_n64<H64>(hc, G4(ST[r >> 1], 0), (r < 4 ? h0 : h1) + (SOFF(r) >> 1), 1);
          }
          wg_commit();
          pred_bar_arrive(7, wg);
          pred_bar_arrive(4, wg == 0);
          TSG(3);
          wg_wait<0>();
          ARRIVE(HHE, 0);
          TSG(4);
#pragma unroll
          for (int i = 0; i < 4; i++) {
            HH[i][0] = pack2(glu(hc[4 * i], hc[16 + 4 * i], ns0, rstd0), glu(hc[4 * i + 1], hc[16 + 4 * i + 1], ns0, rstd0));
            HH[i][1] = pack2(glu(hc[4 * i + 2], hc[16 + 4 * i + 2], ns1, rstd1), glu(hc[4 * i + 3], hc[16 + 4 * i + 3], ns1, rstd1));
          }
          PUBLISH(HH, 0, 2);
          TSG(5);
        } else {
          TS(wg, 13);
        }
        turn_wait(wg);
        mbar_wait(BAR(GUF) + 16u * c);
        TSG(5 + c);
        wg_fence();
        GU_ROW(0, sa);
        GU_ROW(1, sa);
        GU_ROW(2, sa);
        GU_ROW(3, sa);
        wg_commit();
        mbar_wait(BAR(GUF + 1) + 16u * c);
        TSG(24 + c);
        wg_fence();
        GU_ROW(4, sbb);
        wg_commit();
        wg_wait<1>();
        pred_arrive(BAR(GUM - 1) + 8u * c, lane == 0);
        if (EU) {
          int t2;
          asm volatile("mov.u32 %0, %%tid.x;" : "=r"(t2));
          const uint4* sp = &g_h[bid * (14 * 256) + t2];
          const uint4* pp = &g_h[(bid ^ 16) * (14 * 256) + t2];
#define SLOTP(n) ((n) < 12 ? &A[(n) / 3][4 * ((n) % 3)] : ST[(n) - 12])
#pragma unroll
          for (int i = 0; i < 11; i++) {
            const int r = i < 4 ? 5 : i < 7 ? 6 : 7, s = i < 4 ? i : i < 7 ? i - 4 : i - 7;
            if (s < 3) wgmma_rs_n128<H128>(acc, G4(A[r], s), sbb + KOFF(r) + s * 128, 1);
            else wgmma_rs_n128<H128>(acc, G4(ST[r >> 1], 0), sbb + SOFF(r), 1);
#pragma unroll
            for (int n = 0; n < 14; n++)
              if (EU == 1 ? n / 2 == i : EU == 2 ? (n * 11) / 14 == i : EU == 3 ? i == 10 : n / 3 == i) ldg128_pred(n < 6 ? sp + 256 * (5 - n) : pp + 256 * (n - 6), SLOTP(n), c == 2);
          }
        } else {
          GU_ROW(5, sbb);
          GU_ROW(6, sbb);
          GU_ROW(7, sbb);
        }
        wg_commit();
        pred_bar_arrive(7, wg);
        pred_bar_arrive(4, wg == 0);
        wg_wait<0>();
        ARRIVE(GUE, 8u * c);
        TSG(27 + c);
        if (c == 2) break;
      }
      TS(wg, 19);
      if (EU) {
#pragma unroll
        for (int n = 0; n < 14; n++)
#pragma unroll
          for (int k = 0; k < 4; k++) {
            if (n < 6) HH[2 * (5 - n) + (k >> 1)][k & 1] = SLOTP(n)[k];
            else HP[2 * (n - 6) + (k >> 1)][k & 1] = SLOTP(n)[k];
          }
      }
      if (UP == 0) UNPARK();
      if (PEEL) { GLU_CHUNK(20, 2); }
      TS(wg, 14);
      if (UP == 1) UNPARK();
    }
    }
    {
      INDICES();
      const int wg = warp >> 2;
      const bool odd = JMAP(VBID) & 1;
      uint32_t tag;
      LOAD_TAG(tag);
      const uint32_t oA = odd ? 0u : 1536u, oB = odd ? 256u : 0u;
#define DOFF(s, own) ((s) < 2 ? ((own) ? oA : 1536u - oA) + (s) * 128 : ((own) ? oB : 256u - oB) + ((s) - 2) * 128)
      const uint4* hp = &g_h[(bid ^ 16) * (14 * 256) + tid];
      const int lr = (lane & 7) + (lane & 8), lch = lane >> 4;
      const uint32_t stg = cta + SL(1) + wg * SLOT + (warp & 3) * 2048;
      const int oc = odd ? 256 : 0, orow = rb * 128 + warp * 16;
      auto bad = [&](int i0, int n) {
        uint32_t b = 0;
#pragma unroll
        for (int i = i0; i < i0 + n; i++) b = stale(b, HP[2 * i][0], tag);
        return __any_sync(0xffffffffu, b & 1);
      };
#define LOAD_HP(i0, n) _Pragma("unroll") for (int i = i0; i < i0 + (n); i++) ldg128_rlx(hp + 256 * i, AFRAG(HP, i))
#define CHECK_HP(i0, n)                                                                                    \
  if (__builtin_expect(bad(i0, n), 0)) {                                                                   \
    int it_ = 0;                                                                                           \
    do {                                                                                                   \
      LOAD_HP(i0, n);                                                                                      \
      COUNT_FALLBACK(3);                                                                                   \
    } while (bad(i0, n) && ++it_ < SPIN_LIMIT);                                                            \
  }
#define STAGE(d, g, addr) stsm4(addr, pack2(d[8 * g], d[8 * g + 1]), pack2(d[8 * g + 2], d[8 * g + 3]),   \
                                pack2(d[8 * g + 4], d[8 * g + 5]), pack2(d[8 * g + 6], d[8 * g + 7]))
      {
        float da[64], db[32], dc[16];
        mbar_wait(BAR(WDF));
        if (!(PIN & 5)) mbar_wait(BAR(WDF + 1));
        TSD(1);
        turn_wait(wg);
        TSD(2);
        wg_fence();
#pragma unroll
        for (int s = 13; s >= 0; s--) {
          wgmma_rs_n128<H128>(da, AFRAG(HH, s), dlo(SL(2), SLOT) + DOFF(s, 1), s < 13);
          if (UP == 2 && s == 13) { LOAD_HP(8, 2); }
          if (R2 && 13 - s == RW) asm volatile("{\n.reg .pred p;\nsetp.ne.u32 p, %0, 0;\n@p bar.sync 12, 256;\n}" ::"r"(wg) : "memory");
          if (13 - s == LO0) {
            TSD(11);
            CHECK_HP(0, NH);
            LOAD_HP(NH, 14 - NH);
            if (LP) mbar_wait(BAR(WDF));
            wg_fence();
          }
        }
        if (N96) wg_commit();
        TSD(3);
        if (PIN & 4) mbar_wait(BAR(WDF + 1));
        if (LO0 < 0) CHECK_HP(0, NH);
        if (LS < 0 && LO0 < 0) { LOAD_HP(NH, 14 - NH); }
        if (PIN & 1) mbar_wait(BAR(WDF + 1));
        if (RL < 0) pred_bar_arrive(4, wg == 0);
        wg_fence();
#pragma unroll
        for (int s = 0; s < NH; s++) {
          wgmma_rs_n128<H128>(da, AFRAG(HP, s), dlo(SL(6), SLOT) + DOFF(s, 0), 1);
          if (s == RL) pred_bar_arrive(4, wg == 0);
          if (N96 && s == SG) { wg_commit(); wg_wait<1>(); pred_arrive(BAR(SD) + 8u * wg, lane == 0); }
          if (TB == 2 && s == 9) pred_bar_arrive(7, wg);
          if (s == TF) pred_bar_arrive(11, wg);
          if (s == LS) { mbar_wait(BAR(WDF)); LOAD_HP(NH, 14 - NH); mbar_wait(BAR(WDF)); wg_fence(); }
        }
        if (PIN & 2) mbar_wait(BAR(WDF + 2));
        TSD(4);
        CHECK_HP(NH, 14 - NH);
        if (G2 == WOE0 || G3 == WOE0) pred_arrive(BAR(WOE0), lane < 2 && wg == 0);
        TSD(5);
        wg_fence();
#pragma unroll
        for (int s = NH; s < 14; s++) {
          wgmma_rs_n128<H128>(da, AFRAG(HP, s), dlo(SL(6), SLOT) + DOFF(s, 0), 1);
          if (s < 13 && s == RL) pred_bar_arrive(4, wg == 0);
          if (s < 13 && s == TF) pred_bar_arrive(11, wg);
          if (s < 13 && s == R2) pred_bar_arrive(12, wg == 0);
        }
        wg_commit();
        if (RL == 13) pred_bar_arrive(4, wg == 0);
        if (TB == 1) pred_bar_arrive(7, wg);
        if (TF == 13) pred_bar_arrive(11, wg);
        if (R2 == 13) pred_bar_arrive(12, wg == 0);
        if (DW >= 0) pred_bar_arrive(13, wg);
        TSD(6);
        mbar_wait(BAR(GUE + 2) + 24u * wg);
        if (DG == 0) mbar_wait(BAR(IN));
        TSD(7);
        wg_wait<0>();
        TSD(8);
        pred_arrive(BAR(DE), lane == 0 && wg == 0);
#pragma unroll
        for (int g = 0; g < 8; g++) STAGE(da, g, stg + (g >> 2) * 8192 + lr * 128 + ((((2 * g + lch) ^ lane) & 7) << 4));
        fence_async_smem();
        if (DG == 1) {
          ARRIVE(SD, 8u * wg);
        } else {
          __syncwarp();
          if (DG == 2) mbar_wait(BAR(IN));
          tma_red(&maps.out, oc, orow, stg, lane == 0);
          tma_red(&maps.out, oc + 64, orow, stg + 8192, lane == 0);
        }
        TS(wg, 15);
        if (!(PIN & 2)) mbar_wait(BAR(WDF + 2));
        if (TF >= 0) asm volatile("{\n.reg .pred p;\nsetp.eq.u32 p, %0, 0;\n@p bar.sync 11, 256;\n}" ::"r"(wg) : "memory");
        if (TB) asm volatile("{\n.reg .pred p;\nsetp.eq.u32 p, %0, 0;\n@p bar.sync 7, 256;\n}" ::"r"(wg) : "memory");
        if (TD >= 0) asm volatile("{\n.reg .pred p;\nsetp.ne.u32 p, %0, 0;\n@p bar.sync 5, 256;\n}" ::"r"(wg) : "memory");
        TSD(9);
        wg_fence();
#pragma unroll
        for (int s = 0; s < 14; s++) {
          wgmma_rs_n64<H128>(db, AFRAG(HH, s), dlo(SL(4), 0) + DOFF(s, 1), s > 0);
          if (s == DW) asm volatile("{\n.reg .pred p;\nsetp.eq.u32 p, %0, 0;\n@p bar.sync 13, 256;\n}" ::"r"(wg) : "memory");
        }
#pragma unroll
        for (int s = 0; s < 14; s++) {
          wgmma_rs_n64<H128>(db, AFRAG(HP, s), dlo(SL(5), 0) + DOFF(s, 0), 1);
          if (s == TD) pred_bar_arrive(5, wg == 0);
        }
        wg_commit();
        TSD(10);
        if (TC) pred_bar_arrive(7, wg);
        auto mma_c = [&](int s0, int s1) {
          if (s0 == s1) return;
          if (s0 == 0) mbar_wait(BAR(WDF + 3));
          if (TC && s0 == (TC == 1 ? 0 : DS)) asm volatile("{\n.reg .pred p;\nsetp.eq.u32 p, %0, 0;\n@p bar.sync 7, 256;\n}" ::"r"(wg) : "memory");
          if (TE >= 0 && s0 == 0) asm volatile("{\n.reg .pred p;\nsetp.ne.u32 p, %0, 0;\n@p bar.sync 10, 256;\n}" ::"r"(wg) : "memory");
          wg_fence();
#pragma unroll
          for (int s = s0; s < s1; s++) {
            if (s < 14) wgmma_rs_n32<H64>(dc, AFRAG(HH, s), dlo(SL(0), 0) + (DOFF(s, 1) >> 1), s > 0);
            else wgmma_rs_n32<H64>(dc, AFRAG(HP, s - 14), dlo(SL(0) + BLK, 0) + (DOFF(s - 14, 0) >> 1), 1);
            if (s == TE) pred_bar_arrive(10, wg == 0);
          }
          wg_commit();
        };
        mma_c(0, DS < 0 ? 28 : DS);
        if (DG == 1) mbar_wait(BAR(IN));
        if (DS) wg_wait<1>(); else wg_wait<0>();
        TSD(12);
#pragma unroll
        for (int g = 0; g < 4; g++) STAGE(db, g, stg + 16384 + lr * 128 + ((((2 * g + lch) ^ lane) & 7) << 4));
        if (DS >= 0) {
          fence_async_smem();
          __syncwarp();
          tma_red(&maps.out, oc + 128, orow, stg + 16384, lane == 0);
          TSD(13);
          mma_c(DS, 28);
        }
        TS(wg, 16);
        if (DR) {
          uint4* ob = reinterpret_cast<uint4*>(outp + (size_t)(orow + (lane >> 2)) * DM + (odd ? 224 : 192)) + (lane & 3);
          asm volatile("" : "+l"(ob));
          asm volatile("cp.async.bulk.commit_group;" ::: "memory");
          wg_wait<0>();
          uint32_t w[2][4];
#pragma unroll
          for (int i = 0; i < 8; i++) w[i & 1][i >> 1] = pack2(dc[2 * i], dc[2 * i + 1]);
          quad_transpose(w[0], lane);
          quad_transpose(w[1], lane);
          red8(ob, G4(w[0], 0), true);
          red8(ob + DM, G4(w[1], 0), true);
        } else {
        wg_wait<0>();
        const uint32_t st3 = stg + 24576 - (warp & 3) * 1024;
#pragma unroll
        for (int g = 0; g < 2; g++) STAGE(dc, g, st3 + lr * 64 + ((((2 * g + lch) ^ (lane >> 1)) & 3) << 4));
        fence_async_smem();
        __syncwarp();
        if (DS < 0) tma_red(&maps.out, oc + 128, orow, stg + 16384, lane == 0);
        tma_red(&maps.out32, odd ? 224 : 192, orow, st3, lane == 0);
        }
        TS(wg, 17);
        asm volatile("cp.async.bulk.commit_group;\ncp.async.bulk.wait_group.read 0;" ::: "memory");
        TS(wg, 18);
      }
    }
  } else {
    asm volatile("setmaxnreg.dec.sync.aligned.u32 %0;" ::"n"(RLO));
    {
    INDICES();
    const unsigned ep = ld_rlx(&g_ep[bid * 32 + lane]);
#define ZERO_OUT()                                                                                         \
  {                                                                                                        \
    uint4* ob = reinterpret_cast<uint4*>(outp + (size_t)(rb * 128 + 16 * j + (lane >> 2)) * DM) + (lane & 3); \
    _Pragma("unroll 1") for (int b = 11 - warp; b < 7; b += 3)                                             \
      _Pragma("unroll") for (int g = 0; g < 4; g++) stg128(ob + 8 * b + 4 * (g >> 1) + (g & 1) * DM, 0, 0, 0, 0); \
  }
    if (elect()) {
      auto init = [&](int i0, int i1) {
#pragma unroll
        for (int i = i0; i < i1; i++) mbar_init(BAR(i), i < WE || i == RD ? 1 : i < KM + !KMC || i == DE || i >= SD ? 4 : i < XE ? 8 : 16);
#pragma unroll
        for (int i = i0; i < i1; i++)
          if (i < IN)
            mbar_expect(BAR(i), i < WQ0 ? 112 * 112 : i < HAF ? 224 * 112 : N96 && i >= WDF + 2 && i < OF ? SLOT + BLK : i < GUF || i == WDF + 3 ? SLOT : i < OF ? 2 * SLOT
                                : i >= KF ? BLK : (((i - OF) & 3) ? 2 : 1) * (i < HF ? 7168 : CB));
      };
      if (warp == 8) {
        asm volatile("prefetch.tensormap [%0];" ::"l"(&maps.wkv) : "memory");
        init(WS, GUF);
      } else if (warp == 9) {
        init(GUF, 35);
      } else if (warp == 10) {
        init(35, IN);
      } else {
        init(IN, NBAR);
      }
      asm volatile("fence.mbarrier_init.release.cluster;" ::: "memory");
    }
    __syncwarp();
    asm volatile("barrier.cluster.arrive.relaxed.aligned;" ::: "memory");
    asm volatile("barrier.cluster.wait.aligned;" ::: "memory");
    if (warp != 8) {
      if (warp == 9) {
        *s_epoch = ep;
        warp_arrive(BAR(EP), lane);
        if (lane < 14) g_kv[(((ep + 1) & 1) * 8 + j) * KVP + rb * 14 + lane] = make_uint4(0, 0, 0, ((rb * 14 + lane) & 16) ? 0xC180u : 0xC1800000u);
        if (lane < 4) g_z[(ep + 1) & 1][j][rb * 4 + lane] = make_float2(0.f, 0.f);
      } else if (bid < 112) {
        if (PSTART >= 0) mbar_wait(BAR(PSTART));
        const int sg = bid / 7, sr = (bid - 7 * sg) * 4 + (tid >> 4) - 20;
        const uint4* row = reinterpret_cast<const uint4*>(wo_g + (size_t)(112 * (sg >> 2) + 2 * (sg & 3) + 8 * (sr >> 1) + (sr & 1)) * (DM * 2)) + (lane & 15);
        uint32_t a[4][4];
#define SUM8(a) (((bf_lo(a[0]) + bf_hi(a[0])) + (bf_lo(a[1]) + bf_hi(a[1]))) + ((bf_lo(a[2]) + bf_hi(a[2])) + (bf_lo(a[3]) + bf_hi(a[3]))))
#pragma unroll
        for (int i = 0; i < 4; i++) ldg128_nc(row + 16 * i - (i == 3 ? lane & 8 : 0), G4(a[i], 0));
        asm volatile("" : "+r"(a[0][0]), "+r"(a[3][0]));
        float s = (SUM8(a[0]) + SUM8(a[1])) + (SUM8(a[2]) + ((lane & 8) ? 0.f : SUM8(a[3])));
#pragma unroll
        for (int o = 8; o; o >>= 1) s += __shfl_xor_sync(0xffffffffu, s, o);
        s *= 1.f / DM;
        const float hi = bf_lo(pack2(s, 0.f));
        if ((lane & 15) == 0)
          asm volatile("st.relaxed.gpu.global.u32 [%0], %1;" ::"l"(reinterpret_cast<uint32_t*>(g_rs) + (28 * (sg >> 2) + sr) * 4 + (sg & 3)),
                       "r"(tagged(pack2(s - hi, hi), (ep + 1) & 1)) : "memory");
      }
      if (ZI == 1) ZERO_OUT();
    }
    const unsigned tag = (ep + 1) & 1;
    if (warp == 8) {
      if (elect()) {
        const int par = j & 1;
        const int fc = 224 * j + 32 * par;
        const int fh = par ? 224 * j : 224 * j + 192;
        const int k0 = 224 * (j >> 2), k1 = 224 - k0;
        auto ld56 = [&](const CUtensorMap* m, int slot, int c0, int c1, int bar) {
          tma2d_mc(cta + SL(slot) + rank * BLK, m, c0, c1 + rank * 112, BAR(bar));
        };
        auto ld2 = [&](const CUtensorMap* m0, const CUtensorMap* m1, uint32_t d0, uint32_t d1, int x0, int y0, int x1, int y1, int bar) {
          tma2d(cta + d0, m0, x0, y0, BAR(bar));
          tma2d(cta + d1, m1, x1, y1, BAR(bar));
        };
        auto ldgu = [&](int c, int half, int slot) {
          ld2(&maps.wg, &maps.wu, SL(slot), SL(slot + 1), fc + 64 * c, half ? k1 : k0, fc + 64 * c, half ? k1 : k0, GUF + 2 * c + half);
        };
        TS2(3);
        {
          constexpr int ord[] = {ORD};
#pragma unroll
          for (int n = 0; n < (int)(sizeof(ord) / sizeof(int)); n++) {
            const int k = ord[n];
            if (k >= 100) mbar_wait(BAR(k - 100));
            else tma2d_mc(cta + SL(4) + rank * 7168 + k * BLK, &maps.wkv, (k < 4 ? 448 : 896) + 56 * j, 112 * (k & 3) + 56 * rank, BAR(WS + k));
          }
        }
        TS2(1);
        asm volatile("prefetch.tensormap [%0];" ::"l"(&maps.wqkv) : "memory");
        asm volatile("prefetch.tensormap [%0];" ::"l"(&maps.wo) : "memory");
        asm volatile("prefetch.tensormap [%0];" ::"l"(&maps.wg32) : "memory");
        asm volatile("prefetch.tensormap [%0];" ::"l"(&maps.wu32) : "memory");
        asm volatile("prefetch.tensormap [%0];" ::"l"(&maps.wg) : "memory");
        asm volatile("prefetch.tensormap [%0];" ::"l"(&maps.wu) : "memory");
        asm volatile("prefetch.tensormap [%0];" ::"l"(&maps.wd) : "memory");
        asm volatile("prefetch.tensormap [%0];" ::"l"(&maps.wd32) : "memory");
        asm volatile("prefetch.tensormap [%0];" ::"l"(&maps.out) : "memory");
        asm volatile("prefetch.tensormap [%0];" ::"l"(&maps.out32) : "memory");
        mbar_wait(BAR(XE));
        if (DQ) mbar_wait(BAR(DQ));
        TS2(15);
        ld56(&maps.wqkv, 0, 56 * j, 0, WQ0);
        ld56(&maps.wqkv, 1, 56 * j, 224, WQ1);
        mbar_wait(BAR(KE));
        tma4d_mc(cta + SL(4) + rank * BLK, &maps.wo, 56 * j, k0 / 8 + 14 * rank, BAR(WO0));
        tma4d_mc(cta + SL(5) + rank * BLK, &maps.wo, 56 * j, k1 / 8 + 14 * rank, BAR(WO1));
        TS2(16);
        if (EH) {
          mbar_wait(BAR(KM));
          if (EH != KM) mbar_wait(BAR(EH));
          tma2d(cta + SL(7), &maps.wu, fc, k1, BAR(GUF + 1));
        }
        mbar_wait(BAR(KD));
        if (HG) mbar_wait(BAR(HG));
        if (EH) tma2d(cta + SL(6), &maps.wg, fc, k1, BAR(GUF + 1));
        else tma2d_mc(cta + SL(6) + rank * SLOT, rank ? &maps.wu : &maps.wg, fc, k1, BAR(GUF + 1));
        if (PFD) { mbar_wait(BAR(PFD)); l2_prefetch(wd_g + (size_t)bid * 12544, 12544); }
        mbar_wait(BAR(WE));
        if (UG) mbar_wait(BAR(UG));
        ldgu(0, 0, 0);
        mbar_wait(BAR(HE));
        if (H2) mbar_wait(BAR(H2));
        ld2(&maps.wg32, &maps.wu32, SL(4), SL(4) + BLK, fh, k0, fh, k0, HAF);
        ld2(&maps.wg32, &maps.wu32, SL(5), SL(5) + BLK, fh, k1, fh, k1, HBF);
        mbar_wait(BAR(HE + 1));
        ldgu(1, 0, 2);
        mbar_wait(BAR(GUE));
        ldgu(1, 1, 6);
        if (O5) ldgu(2, 1, 0);
        mbar_wait(BAR(HHE));
        ldgu(2, 0, 4);
        if (!O5) ldgu(2, 1, 0);
        {
          const int dc = 256 * par, ro = 224 * j, rp = 224 * (j ^ 1);
          mbar_wait(BAR(GUM));
          ld2(&maps.wd, &maps.wd, SL(2), SL(3), dc, ro, dc + 64, ro, WDF);
          mbar_wait(BAR(GUE + 1));
          ld2(&maps.wd, &maps.wd, SL(6), SL(7), dc, rp, dc + 64, rp, WDF + 1);
          mbar_wait(BAR(GUM + 1));
          if (G2) mbar_wait(BAR(G2));
          if (N96) ld2(&maps.wd, &maps.wd32, SL(4), SL(5), dc + 128, ro, 192 + 32 * par, ro, WDF + 2);
          else ld2(&maps.wd, &maps.wd, SL(4), SL(5), dc + 128, ro, dc + 128, rp, WDF + 2);
          mbar_wait(BAR(GUE + 2));
          if (G3) mbar_wait(BAR(G3));
          if (N96) {
            tma2d(cta + SL(0), &maps.wd, dc + 128, rp, BAR(WDF + 3));
            mbar_wait(BAR(SD));
            mbar_wait(BAR(SD + 1));
            tma2d(cta + SL(3), &maps.wd32, 192 + 32 * par, rp, BAR(WDF + 3));
          } else {
            ld2(&maps.wd32, &maps.wd32, SL(0), SL(0) + BLK, 192 + 32 * par, ro, 192 + 32 * par, rp, WDF + 3);
          }
        }
      }
    } else if (warp == 9) {
      const bool kl = lane >= 16;
      const unsigned target = kl ? 0x41800000u : (ep + 1) << 2;
      const int n = lane < 14 ? lane : 0;
      const int w = n >= 7, hi = n - 7 * w;
      const int hb = (rb * 8 + (j ^ (hi + 1))) * 2 + w;
      const uint4* kv = &g_kv[((ep & 1) * 8 + ((j & 4) ^ (lane & 7))) * KVP];
      mbar_wait(BAR(KM));
      if (RSTART != KM) mbar_wait(BAR(RSTART));
      g_ep[bid * 32 + lane] = ep + 1;
#pragma unroll 1
      for (int ph = 0; ph < 2; ph++) {
        const unsigned* flag = kl && !ph ? reinterpret_cast<const unsigned*>(&g_z[ep & 1][lane & 7][47].y) : &g_flag[ph * 512 + rb * 16 + hb];
        const void* gsrc = kl ? (const void*)kv : (const void*)&g_x[(ph * 256 + hb) * (HB / 16)];
        const uint32_t fbar = kl ? BAR(KF) + (lane & 4) * 2 : BAR(OF + 8 * ph + 4 * w + ((hi + 1) >> 1));
        const uint32_t ebar = BAR(ph ? w ? WE + 1 : W0 && n < 3 ? WOE0 : WOE1 : kl ? KM : QE);
        const uint32_t dst = kl ? cta + SL(6) + (lane & 4) * (BLK / 4) : cta + sb + n * HB + (ph > w) * (4 * SLOT);
        bool done = lane >= 14 && (ph || (lane & 24) != 16);
        bool rdy = done;
        done = done || (kl && (KMC ? (lane & 7) != 4 * rank : (lane & 3) != 0));
        unsigned pend = 0x7fu, fv = target - 1;
#pragma unroll 1
        for (int it = 0; it < SPIN_LIMIT; it++) {
          if (PP) {
            rdy = rdy || (int)(fv - target) >= 0;
            if (!rdy) fv = ld_rlx(flag);
          } else {
            rdy = rdy || (int)(ld_rlx(flag) - target) >= 0;
          }
          const bool ok = rdy && mbar_test(ebar) && (!((WG >> ph) & 1) || w == 0 || mbar_test(BAR(OF + WW) + 64u * ph));
          const unsigned rm = __ballot_sync(0xffffffffu, rdy);
          const bool kall = kl ? !KALL || (rm >> 16) == 0xffffu : !((CALL >> ph) & 1) || (rm & 0x7fu) == 0x7fu;
          if ((GW >> ph) & 1) pend = __ballot_sync(0xffffffffu, !done && !ok);
          if (!done && ok && kall && (w == 0 || (pend & 0x7fu) == 0)) {
            if (KMC == 1) bulk_load_mc(dst, gsrc, kl ? BLK : HB, fbar, kl ? 3 : 1 + rank);
            else if (KMC && kl) bulk_load_mc(dst, gsrc, BLK, fbar, 3);
            else bulk_load(dst, gsrc, kl ? BLK : 7168 + ph * (CB - 7168), fbar);
            done = true;
          }
          pend = __ballot_sync(0xffffffffu, !done);
          if (pend == 0) break;
          if (KW >= 0 && pend < 0x10000u) mbar_wait(BAR(KF + KW));
        }
        pred_arrive(BAR(RD), (lane | ph) == 0);
        if (lane == 0) TS2(14 + 4 * ph);
      }
    } else if (warp == 10) {
      if (lane == 0) {
        mbar_wait(BAR(PFT));
        l2_prefetch(wg_g + (size_t)bid * 12544, 12544);
        l2_prefetch(wu_g + (size_t)bid * 12544, 12544);
        if (!PFD) l2_prefetch(wd_g + (size_t)bid * 12544, 12544);
      }
      __syncwarp();
      mbar_wait(BAR(ZSTART));
      const float2* zp = &g_z[ep & 1][j][2 * (lane < 28 ? lane : 0)];
      uint32_t z0, c0, z1, c1;
      int it = 0;
      do {
        ldg128_rlx(zp, z0, c0, z1, c1);
      } while ((c0 & c1) != 0x41800000u && ++it < SPIN_LIMIT);
      TS2(11);
      {
        const uint32_t a = cta + sb + Z_OFF + (lane & 16) * 8 + (lane & 3) * 16 + (lane & 12) + (lane < 14 ? 0 : 64);
        asm volatile("st.shared.u32 [%0], %1;\nst.shared.u32 [%2], %3;" ::"r"(a),
                     "r"(lane < 28 ? pack2(__uint_as_float(z0), __uint_as_float(z1)) : 0u), "r"(a ^ 64), "r"(0) : "memory");
      }
      warp_arrive(BAR(ZF), lane);
      TS2(6);
    } else {
      TS2(9);
      mbar_wait(BAR(RP));
      TS2(10);
      if (lane < 28) {
        uint32_t v[4][4], b;
        int it = 0;
        do {
          b = 0;
#pragma unroll
          for (int h = 0; h < 4; h++) ldg128_rlx(&g_rs[28 * h + lane], G4(v[h], 0));
#pragma unroll
          for (int h = 0; h < 16; h++) b = stale(b, v[h >> 2][h & 3], tag);
        } while ((b & 1) && ++it < SPIN_LIMIT);
        TS2(7);
        if (RP != KE) mbar_wait(BAR(KE));
        const uint32_t a = cta + SL(4) + lane * 128 + ((7 ^ (lane & 7)) << 4);
#pragma unroll
        for (int h = 0; h < 4; h++)
#pragma unroll
          for (int t = 0; t < 4; t++)
            sts128((a ^ ((t & 1) * 64)) + (((h >> 1) ^ (j >> 2)) * 2 + (h & 1)) * BLK + t * 3584, v[h][t], v[h][t], v[h][t], v[h][t]);
        TS2(8);
      }
      mbar_wait(BAR(WO0));
      mbar_wait(BAR(WO1));
      warp_arrive(BAR(RS), lane);
      TS2(5);
    }
    }
    __syncwarp();
    if (threadIdx.x >= 288) {
      INDICES();
      const char* cb = reinterpret_cast<const char*>(&g_x[(256 + rb * 16 + (j >> 2)) * (HB / 16) + (j & 3) * 32 + lane]);
      uint4* ob = reinterpret_cast<uint4*>(outp + (size_t)(rb * 128 + 16 * j + (lane >> 2)) * DM) + (lane & 3);
      if (ZI == 2) ZERO_OUT();
      unsigned* cnt = &g_flag[1024 + rb * 32];
      if (ZI) {
        __syncwarp();
        if (lane == 0) asm volatile("red.release.gpu.global.add.u32 [%0], 1;" ::"l"(cnt) : "memory");
        if (tid == 320) TS2(22);
      }
      mbar_wait(BAR(HE) + 8u * (j >> 2));
      if (tid == 320) TS2(19);
      float m0, m1;
      asm volatile("ld.shared.v2.f32 {%0, %1}, [%2];" : "=f"(m0), "=f"(m1) : "r"(cta + sb + MST_OFF + lane * 8) : "memory");
#pragma unroll 1
      for (int b = 11 - warp; b < 7; b += 3) {
        uint32_t h[2][8];
#pragma unroll
        for (int t = 0; t < 8; t++) {
          const int o = c_off[8 * b + t];
          ldg64_rlx(cb + (C7 && (o & 6144) == 6144 ? o - ((j & 3) * 32 + lane) * 8 : o), h[0][t], h[1][t]);
        }
#pragma unroll
        for (int t = 0; t < 8; t++) {
          h[0][t] = pack2(bf_lo(h[0][t]) + m0, bf_hi(h[0][t]) + m0);
          h[1][t] = pack2(bf_lo(h[1][t]) + m1, bf_hi(h[1][t]) + m1);
        }
#pragma unroll
        for (int g = 0; g < 4; g++) {
          uint32_t* w = &h[g & 1][4 * (g >> 1)];
#pragma unroll
          for (int x = 1; x < 4; x <<= 1)
#pragma unroll
            for (int i = 0; i < 2; i++) {
              const int lo = x == 1 ? 2 * i : i;
              const uint32_t r = __shfl_xor_sync(0xffffffffu, (lane & x) ? w[lo] : w[lo + x], x);
              if (lane & x) w[lo] = r; else w[lo + x] = r;
            }
          if (ZI) red8(ob + 8 * b + 4 * (g >> 1) + (g & 1) * DM, w[0], w[1], w[2], w[3], true);
          else ob[8 * b + 4 * (g >> 1) + (g & 1) * DM] = make_uint4(w[0], w[1], w[2], w[3]);
        }
      }
      __syncwarp();
      if (lane == 0) {
        if (warp == 10) TS2(21);
        if (!ZI) asm volatile("red.release.gpu.global.add.u32 [%0], 1;" ::"l"(cnt) : "memory");
        if (!ZI && warp == 10) TS2(22);
        if (warp == 10) {
          const unsigned target = (*s_epoch + 1) * 24;
          unsigned f;
          int it = 0;
          do {
            asm volatile("ld.acquire.gpu.global.u32 %0, [%1];" : "=r"(f) : "l"(cnt) : "memory");
          } while ((int)(f - target) < 0 && ++it < SPIN_LIMIT);
          TS2(23);
          asm volatile("fence.proxy.async.global;" ::: "memory");
          mbar_arrive(BAR(IN));
          TS2(20);
        }
      }
    }
  }
}
typedef CUresult (*EncFn)(CUtensorMap*, CUtensorMapDataType, cuuint32_t, void*, const cuuint64_t*, const cuuint64_t*,
                          const cuuint32_t*, const cuuint32_t*, CUtensorMapInterleave, CUtensorMapSwizzle,
                          CUtensorMapL2promotion, CUtensorMapFloatOOBfill);

void make_map(EncFn enc, CUtensorMap* m, const void* p, int cols, int rows, int bc, int br, CUtensorMapSwizzle sw,
              CUtensorMapL2promotion pr = CU_TENSOR_MAP_L2_PROMOTION_L2_128B) {
  cuuint64_t gd[2] = {(cuuint64_t)cols, (cuuint64_t)rows};
  cuuint64_t gs[1] = {(cuuint64_t)cols * 2};
  cuuint32_t box[2] = {(cuuint32_t)bc, (cuuint32_t)br};
  cuuint32_t es[2] = {1, 1};
  enc(m, CU_TENSOR_MAP_DATA_TYPE_BFLOAT16, 2, const_cast<void*>(p), gd, gs, box, es, CU_TENSOR_MAP_INTERLEAVE_NONE, sw,
      pr, CU_TENSOR_MAP_FLOAT_OOB_FILL_NONE);
}

}

extern "C" void kernel_launch(void* const* d_in, const int* in_sizes, int n_in, void* d_out, int out_size) {
  static EncFn enc = nullptr;
  if (!enc) {
    void* fn = nullptr;
    cudaDriverEntryPointQueryResult qr;
    cudaGetDriverEntryPoint("cuTensorMapEncodeTiled", &fn, cudaEnableDefault, &qr);
    enc = (EncFn)fn;
    cudaFuncSetAttribute(fused_kernel, cudaFuncAttributeMaxDynamicSharedMemorySize, SMEM_BYTES);
  }
  Maps maps;
  make_map(enc, &maps.x, d_in[0], DM, SEQ, 64, 128, CU_TENSOR_MAP_SWIZZLE_128B, CU_TENSOR_MAP_L2_PROMOTION_L2_256B);
  make_map(enc, &maps.wkv, d_in[1], 3 * DM, DM, 56, 56, CU_TENSOR_MAP_SWIZZLE_128B, CU_TENSOR_MAP_L2_PROMOTION_L2_256B);
  make_map(enc, &maps.wqkv, d_in[1], 3 * DM, DM, 56, 112, CU_TENSOR_MAP_SWIZZLE_128B);
  {
    cuuint64_t gd[4] = {DM, 2, DM / 8, 4}, gs[3] = {DM * 2, DM * 16, DM * 4};
    cuuint32_t box[4] = {56, 2, 14, 4}, es[4] = {1, 1, 1, 1};
    enc(&maps.wo, CU_TENSOR_MAP_DATA_TYPE_BFLOAT16, 4, d_in[2], gd, gs, box, es, CU_TENSOR_MAP_INTERLEAVE_NONE,
        CU_TENSOR_MAP_SWIZZLE_128B, CU_TENSOR_MAP_L2_PROMOTION_L2_128B, CU_TENSOR_MAP_FLOAT_OOB_FILL_NONE);
  }
  make_map(enc, &maps.wg, d_in[4], FF, DM, 64, 224, CU_TENSOR_MAP_SWIZZLE_128B);
  make_map(enc, &maps.wu, d_in[5], FF, DM, 64, 224, CU_TENSOR_MAP_SWIZZLE_128B);
  make_map(enc, &maps.wg32, d_in[4], FF, DM, 32, 224, CU_TENSOR_MAP_SWIZZLE_64B);
  make_map(enc, &maps.wu32, d_in[5], FF, DM, 32, 224, CU_TENSOR_MAP_SWIZZLE_64B);
  make_map(enc, &maps.wd, d_in[6], DM, FF, 64, 224, CU_TENSOR_MAP_SWIZZLE_128B);
  make_map(enc, &maps.wd32, d_in[6], DM, FF, 32, 224, N96 ? CU_TENSOR_MAP_SWIZZLE_128B : CU_TENSOR_MAP_SWIZZLE_64B);
  make_map(enc, &maps.out, d_out, DM, SEQ, 64, 16, CU_TENSOR_MAP_SWIZZLE_128B);
  make_map(enc, &maps.out32, d_out, DM, SEQ, 32, 16, CU_TENSOR_MAP_SWIZZLE_64B);
  fused_kernel<<<128, 384, SMEM_BYTES, cudaStreamPerThread>>>(maps, (const char*)d_in[0], (const char*)d_in[2], (const char*)d_in[4], (const char*)d_in[5],
                                                             (const char*)d_in[6], (__nv_bfloat16*)d_out);
}
```
